```python
import torch

def _softmax(x, axis=-1):
    return torch.softmax(x, dim=axis)

def _gelu(x):
    return torch.nn.functional.gelu(x, approximate='tanh')

def _silu(x):
    return torch.nn.functional.silu(x)

def _sigmoid(x):
    return torch.sigmoid(x)

def _layernorm(x, axis=-1, eps=1e-05):
    m = x.mean(dim=axis, keepdim=True)
    v = x.var(dim=axis, keepdim=True, unbiased=False)
    return (x - m) / torch.sqrt(v + eps)

def _scatter_add(tgt, idx, src, axis=0):
    return tgt.clone().index_add_(axis, idx, src)

def _segment_sum(src, seg, n):
    out = torch.zeros((n,) + src.shape[1:], dtype=src.dtype)
    return out.index_add_(0, seg, src)

def _pad(x, pw):
    flat = tuple((v for pair in reversed(pw) for v in pair))
    return torch.nn.functional.pad(x, flat)
kernel_name = 'adaLN_cond__mha_block_cached__geglu_ffn__decode'

def setup_inputs():

    _w = lambda a: (lambda t: t.to(torch.bfloat16) if t.is_floating_point() else t)(torch.as_tensor(a))

    def _A_setup():
        B, Sq, D = (1, 1, 512)
        H, Sk, Dh = (32, 65536, 128)
        return {'x': _w((lambda *s: torch.randn(*s, dtype=torch.bfloat16) * 0.1)(B, Sq, D)), 'k_cache': _w((lambda *s: torch.randn(*s, dtype=torch.bfloat16) * 0.8)(B, H, Sk, Dh)), 'v_cache': _w((lambda *s: torch.randn(*s, dtype=torch.bfloat16) * 1.6)(B, H, Sk, Dh)), 'wq': _w((lambda *s: torch.randn(*s, dtype=torch.bfloat16) * 0.8)(D, H * Dh) * D ** (-0.5)), 'wo': _w((lambda *s: torch.randn(*s, dtype=torch.bfloat16) * 1.6)(H * Dh, D) * (H * Dh) ** (-0.5))}
    _A_in = _A_setup()

    def _B_setup():
        B, S, D, F = (1, 1, 512, 1792)
        return {'x': _w((lambda *s: torch.randn(*s, dtype=torch.bfloat16) * 0.1)(B, S, D)), 'w_gate': _w((lambda *s: torch.randn(*s, dtype=torch.bfloat16) * 0.4)(D, F)), 'w_up': _w((lambda *s: torch.randn(*s, dtype=torch.bfloat16) * 0.4)(D, F)), 'w_down': _w((lambda *s: torch.randn(*s, dtype=torch.bfloat16) * 0.4)(F, D))}
    _B_in = _B_setup()
    return {'A_x': _A_in['x'], 'A_k_cache': _A_in['k_cache'], 'A_v_cache': _A_in['v_cache'], 'A_wq': _A_in['wq'], 'A_wo': _A_in['wo'], 'B_x': _B_in['x'], 'B_w_gate': _B_in['w_gate'], 'B_w_up': _B_in['w_up'], 'B_w_down': _B_in['w_down'], 'c': _w((lambda *s: torch.randn(*s, dtype=torch.bfloat16) * 0.4)(1, 512) * 8.0), 'w_mod': _w((lambda *s: torch.randn(*s, dtype=torch.bfloat16) * 0.4)(512, 6 * 512) * 512 ** (-0.5) * 8.0)}

def reference(A_x, A_k_cache, A_v_cache, A_wq, A_wo, B_x, B_w_gate, B_w_up, B_w_down, c, w_mod):

    def _A_ref(x, k_cache, v_cache, wq, wo):
        B, Sq, D = x.shape
        H, Dh = (32, 128)
        q = (lambda x, *d: x.permute(*d))((x @ wq).reshape(B, Sq, H, Dh), 0, 2, 1, 3)
        scores = torch.einsum('bhqd,bhkd->bhqk', q, k_cache) * Dh ** (-0.5)
        p = _softmax(scores, axis=-1)
        o = torch.einsum('bhqk,bhkd->bhqd', p, v_cache)
        return (lambda x, *d: x.permute(*d))(o, 0, 2, 1, 3).reshape(B, Sq, H * Dh) @ wo

    def _B_ref(x, w_gate, w_up, w_down):
        return _gelu(x @ w_gate) * (x @ w_up) @ w_down
    x = A_x
    mod = (_silu(c) @ w_mod).reshape(c.shape[0], 6, 1, -1)
    sa, ca, ga, sb, cb, gb = (mod[:, 0].clone(), mod[:, 1].clone(), mod[:, 2].clone(), mod[:, 3].clone(), mod[:, 4].clone(), mod[:, 5].clone())
    h = _layernorm(x, axis=-1) * (1 + ca) + sa
    x = x + ga * _A_ref(h, A_k_cache, A_v_cache, A_wq, A_wo)
    h = _layernorm(x, axis=-1) * (1 + cb) + sb
    x = x + gb * _B_ref(h, B_w_gate, B_w_up, B_w_down)
    return x
```

```cpp
#include <cuda_runtime.h>
#include <cuda_bf16.h>
#include <cuda.h>
#include <stdint.h>
#include <stdio.h>

namespace {

typedef unsigned long long u64;

constexpr int D_MODEL = 512;
constexpr int NHEAD = 32;
constexpr int SEQ = 65536;
constexpr int DH = 128;
constexpr int FF = 1792;
constexpr int GRID = 132;

constexpr int TILE = 32;
constexpr int TPH = SEQ / TILE;
constexpr int TPH_SHIFT = 11;
constexpr int NTILES = NHEAD * TPH;
#define NST 8
#define EARLY_GATE 0
#define IF_EARLY 2
#define INFLIGHT 6
constexpr int STAGE_BYTES = TILE * DH * 2 * 2;
constexpr int NCW = 4;
constexpr int NTHREADS = 320;

constexpr int MOD0_CTAS = 32;
constexpr int MOD_CTAS = 96;
constexpr int Q_CTAS = 128;
constexpr int FFN_CTAS = 112;

constexpr int WROW = 1040;
constexpr int SM_KV = 0;
constexpr int SM_WO = SM_KV + NST * STAGE_BYTES;
constexpr int SM_WD = SM_WO + 32 * WROW;
constexpr int SM_WGU = SM_WD + 16 * WROW;
constexpr int SM_QS = SM_WGU + 512 * 64;
constexpr int SM_FL = SM_QS + 8192;
constexpr int SM_VEC = SM_FL + 2 * 4 * 132 * 4;
constexpr int SM_RED = SM_VEC + 1024;
constexpr int SM_STAT = SM_RED + 512;
constexpr int SM_FIN = SM_STAT + 64;
constexpr int SM_BAR = SM_FIN + 64;
constexpr int SM_INFO = SM_BAR + (2 * NST + 10) * 8;
constexpr int SM_TOTAL = SM_INFO + NST * 4;
static_assert(SM_TOTAL <= 232448, "shared memory budget");
static_assert(SM_BAR % 8 == 0 && SM_STAT % 16 == 0, "alignment");

__device__ unsigned g_epoch;
__device__ unsigned g_ctr;
__device__ __align__(128) u64 g_mod[1536];
__device__ __align__(128) u64 g_q[2048];
__device__ __align__(128) uint32_t g_po[NHEAD * 4 * GRID * 32];
__device__ __align__(128) uint32_t g_ph[NHEAD * GRID * 2];
__device__ __align__(128) uint32_t g_R[NHEAD * 4 * D_MODEL];
__device__ __align__(128) uint32_t g_f[FFN_CTAS * D_MODEL];
#define TS(i) do { } while (0)
#define CKS(i) do { } while (0)
#define TSW(i) do { } while (0)

constexpr float LOG2E = 1.4426950408889634f;
constexpr unsigned SPIN_LIMIT = 1u << 24;

__device__ __forceinline__ uint32_t smem_u32(const void* p) { return (uint32_t)__cvta_generic_to_shared(p); }
__device__ __forceinline__ void mbar_init(uint32_t bar, uint32_t cnt) {
    asm volatile("mbarrier.init.shared::cta.b64 [%0], %1;" ::"r"(bar), "r"(cnt) : "memory");
}
__device__ __forceinline__ void mbar_expect_tx(uint32_t bar, uint32_t bytes) {
    asm volatile("mbarrier.arrive.expect_tx.shared::cta.b64 _, [%0], %1;" ::"r"(bar), "r"(bytes) : "memory");
}
__device__ __forceinline__ void mbar_arrive(uint32_t bar) {
    asm volatile("mbarrier.arrive.shared::cta.b64 _, [%0];" ::"r"(bar) : "memory");
}
__device__ __forceinline__ void mbar_wait(uint32_t bar, uint32_t parity) {
    unsigned spins = 0;
    while (true) {
        uint32_t ok;
        asm volatile(
            "{\n.reg .pred p;\n"
            "mbarrier.try_wait.parity.shared::cta.b64 p, [%1], %2;\n"
            "selp.u32 %0, 1, 0, p;\n}"
            : "=r"(ok)
            : "r"(bar), "r"(parity)
            : "memory");
        if (ok) break;
        if (++spins > SPIN_LIMIT) __trap();
    }
}
__device__ __forceinline__ void bar_sync(int id, int n) { asm volatile("bar.sync %0, %1;" ::"r"(id), "r"(n) : "memory"); }
__device__ __forceinline__ void hbar() { asm volatile("bar.sync 1, 128;" ::: "memory"); }

__device__ __forceinline__ void tma_tile(uint32_t dst, const CUtensorMap* m, int key, uint32_t bar, u64 pol) {
    asm volatile(
        "cp.async.bulk.tensor.3d.shared::cluster.global.mbarrier::complete_tx::bytes.L2::cache_hint "
        "[%0], [%1, {%3, %4, %3}], [%2], %5;"
        ::"r"(dst), "l"(m), "r"(bar), "r"(0), "r"(key), "l"(pol)
        : "memory");
}
__device__ __forceinline__ void bulk_g2s(uint32_t dst, const void* src, uint32_t bytes, uint32_t bar) {
    asm volatile("cp.async.bulk.shared::cluster.global.mbarrier::complete_tx::bytes [%0], [%1], %2, [%3];"
                 ::"r"(dst), "l"(src), "r"(bytes), "r"(bar) : "memory");
}
__device__ __forceinline__ void cp_async16(uint32_t dst, const void* src) {
    asm volatile("cp.async.cg.shared.global [%0], [%1], 16;" ::"r"(dst), "l"(src) : "memory");
}
__device__ __forceinline__ void cp_async_commit() { asm volatile("cp.async.commit_group;" ::: "memory"); }
__device__ __forceinline__ void ll_store(u64* p, uint32_t data, uint32_t flag, uint32_t live = 1) {
    u64 v = ((u64)flag << 32) | data;
    asm volatile("{\n.reg .pred p;\nsetp.ne.u32 p, %2, 0;\n@p st.relaxed.gpu.global.u64 [%0], %1;\n}" ::"l"(p), "l"(v), "r"(live) : "memory");
}
__device__ __forceinline__ void ll_load(const u64* p, u64& a, uint32_t live = 1) {
    asm volatile("{\n.reg .pred p;\nsetp.ne.u32 p, %2, 0;\n@p ld.relaxed.gpu.global.u64 %0, [%1];\n}" : "+l"(a) : "l"(p), "r"(live) : "memory");
}
__device__ __forceinline__ void ll_load2(const u64* p, u64& a, u64& b, uint32_t live = 1) {
    asm volatile("{\n.reg .pred p;\nsetp.ne.u32 p, %3, 0;\n@p ld.relaxed.gpu.global.v2.u64 {%0,%1}, [%2];\n}"
                 : "+l"(a), "+l"(b) : "l"(p), "r"(live) : "memory");
}
__device__ __forceinline__ uint32_t tg_enc(float v, uint32_t tag) { return (__float_as_uint(v) & ~3u) | tag; }
__device__ __forceinline__ float tg_dec(uint32_t v) { return __uint_as_float(v & ~3u); }
__device__ __forceinline__ void tg_store(uint32_t* p, float v, uint32_t tag, uint32_t live = 1) {
    asm volatile("{\n.reg .pred p;\nsetp.ne.u32 p, %2, 0;\n@p st.relaxed.gpu.global.u32 [%0], %1;\n}" ::"l"(p), "r"(tg_enc(v, tag)), "r"(live) : "memory");
}
__device__ __forceinline__ void tg_load(const uint32_t* p, uint32_t& a, uint32_t live) {
    asm volatile("{\n.reg .pred p;\nsetp.ne.u32 p, %2, 0;\n@p ld.relaxed.gpu.global.u32 %0, [%1];\n}" : "+r"(a) : "l"(p), "r"(live) : "memory");
}
__device__ __forceinline__ void tg_load2(const uint32_t* p, uint32_t& a, uint32_t& b, uint32_t live) {
    asm volatile("{\n.reg .pred p;\nsetp.ne.u32 p, %3, 0;\n@p ld.relaxed.gpu.global.v2.u32 {%0,%1}, [%2];\n}"
                 : "+r"(a), "+r"(b) : "l"(p), "r"(live) : "memory");
}
__device__ __forceinline__ void tg_load4(const uint32_t* p, uint4& v, uint32_t live) {
    asm volatile("{\n.reg .pred p;\nsetp.ne.u32 p, %5, 0;\n@p ld.relaxed.gpu.global.v4.u32 {%0,%1,%2,%3}, [%4];\n}"
                 : "+r"(v.x), "+r"(v.y), "+r"(v.z), "+r"(v.w) : "l"(p), "r"(live) : "memory");
}
__device__ __forceinline__ uint32_t tg_bad4(const uint4& v, uint32_t tag) { return ((v.x ^ tag) | (v.y ^ tag) | (v.z ^ tag) | (v.w ^ tag)) & 3u; }
__device__ __forceinline__ bool ll_ok(u64 v, uint32_t flag) { return (uint32_t)(v >> 32) == flag; }

__device__ __forceinline__ void ldsm4(uint32_t (&r)[4], uint32_t addr) {
    asm volatile("ldmatrix.sync.aligned.m8n8.x4.shared.b16 {%0,%1,%2,%3}, [%4];"
                 : "=r"(r[0]), "=r"(r[1]), "=r"(r[2]), "=r"(r[3]) : "r"(addr) : "memory");
}
__device__ __forceinline__ void ldsm4t(uint32_t (&r)[4], uint32_t addr) {
    asm volatile("ldmatrix.sync.aligned.m8n8.x4.trans.shared.b16 {%0,%1,%2,%3}, [%4];"
                 : "=r"(r[0]), "=r"(r[1]), "=r"(r[2]), "=r"(r[3]) : "r"(addr) : "memory");
}
__device__ __forceinline__ void mma16816(float (&d)[4], const uint32_t (&a)[4], uint32_t b0, uint32_t b1) {
    asm volatile(
        "mma.sync.aligned.m16n8k16.row.col.f32.bf16.bf16.f32 {%0,%1,%2,%3}, {%4,%5,%6,%7}, {%8,%9}, {%0,%1,%2,%3};"
        : "+f"(d[0]), "+f"(d[1]), "+f"(d[2]), "+f"(d[3])
        : "r"(a[0]), "r"(a[1]), "r"(a[2]), "r"(a[3]), "r"(b0), "r"(b1));
}
__device__ __forceinline__ uint32_t movm(uint32_t a) {
    uint32_t d;
    asm volatile("movmatrix.sync.aligned.m8n8.trans.b16 %0, %1;" : "=r"(d) : "r"(a));
    return d;
}
__device__ __forceinline__ uint32_t pack_bf16(float lo, float hi) {
    uint32_t d;
    asm("cvt.rn.bf16x2.f32 %0, %1, %2;" : "=r"(d) : "f"(hi), "f"(lo));
    return d;
}
__device__ __forceinline__ float bf_lo(uint32_t v) { return __uint_as_float(v << 16); }
__device__ __forceinline__ float bf_hi(uint32_t v) { return __uint_as_float(v & 0xffff0000u); }
__device__ __forceinline__ float rbf(float x) { return bf_lo(pack_bf16(x, x)); }
__device__ __forceinline__ float ex2(float x) {
    float y;
    asm("ex2.approx.ftz.f32 %0, %1;" : "=f"(y) : "f"(x));
    return y;
}
__device__ __forceinline__ float silu_bf(float c) { return rbf(__fdividef(c, 1.f + __expf(-c))); }
__device__ __forceinline__ float warp_sum(float v) {
#pragma unroll
    for (int o = 16; o > 0; o >>= 1) v += __shfl_xor_sync(0xffffffffu, v, o);
    return v;
}
__device__ __forceinline__ float warp_max(float v) {
#pragma unroll
    for (int o = 16; o > 0; o >>= 1) v = fmaxf(v, __shfl_xor_sync(0xffffffffu, v, o));
    return v;
}

__device__ __forceinline__ float4 layernorm512(float4 x, float2* stat) {
    const int tid = threadIdx.x;
    float m = ((x.x + x.y) + (x.z + x.w)) * 0.25f;
    const float d0 = x.x - m, d1 = x.y - m, d2 = x.z - m, d3 = x.w - m;
    float q = (d0 * d0 + d1 * d1) + (d2 * d2 + d3 * d3);
#pragma unroll
    for (int r = 0; r < 5; r++) {
        const float mo = __shfl_xor_sync(0xffffffffu, m, 16 >> r);
        const float qo = __shfl_xor_sync(0xffffffffu, q, 16 >> r);
        const float dl = mo - m;
        m = fmaf(dl, 0.5f, m);
        q = fmaf(dl * dl, (float)(2 << r), q + qo);
    }
    if ((tid & 31) == 0) stat[(tid >> 5) & 3] = make_float2(m, q);
    hbar();
    const float4 s01 = *reinterpret_cast<const float4*>(stat), s23 = *reinterpret_cast<const float4*>(stat + 2);
    const float da = s01.z - s01.x, db = s23.z - s23.x;
    const float ma = fmaf(da, 0.5f, s01.x), mb = fmaf(db, 0.5f, s23.x);
    const float qa = fmaf(da * da, 64.f, s01.y + s01.w), qb = fmaf(db * db, 64.f, s23.y + s23.w);
    const float dc = mb - ma;
    const float mean = rbf(fmaf(dc, 0.5f, ma));
    const float var = rbf(fmaf(dc * dc, 128.f, qa + qb) * (1.f / 512.f));
    float den;
    asm("sqrt.approx.f32 %0, %1;" : "=f"(den) : "f"(rbf(var + 1e-5f)));
    den = rbf(den);
    float4 y;
    y.x = rbf(__fdividef(rbf(x.x - mean), den));
    y.y = rbf(__fdividef(rbf(x.y - mean), den));
    y.z = rbf(__fdividef(rbf(x.z - mean), den));
    y.w = rbf(__fdividef(rbf(x.w - mean), den));
    return y;
}

__device__ __noinline__ float gemv512x32(uint32_t wbase, const uint32_t* vec, float* red) {
    const int lane = threadIdx.x & 31, hw = (threadIdx.x >> 5) & 3;
    const int g = lane >> 2, t4 = lane & 3, mi = lane >> 3, rr = lane & 7;
    float c0[2][4], c1[2][4];
#pragma unroll
    for (int i = 0; i < 2; i++) { c0[i][0] = c0[i][1] = c0[i][2] = c0[i][3] = 0.f; c1[i][0] = c1[i][1] = c1[i][2] = c1[i][3] = 0.f; }
    const int row0 = hw * 128 + (mi >> 1) * 8 + rr;
    const int sw = (row0 >> 1) & 3;
    const uint32_t a0 = wbase + row0 * 64 + (((mi & 1) ^ sw) << 4);
    const uint32_t a1 = wbase + row0 * 64 + (((2 + (mi & 1)) ^ sw) << 4);
    const uint32_t* vp = vec + hw * 64 + t4;
#pragma unroll
    for (int ks = 0; ks < 8; ks++) {
        const uint32_t b0 = vp[ks * 8], b1 = vp[ks * 8 + 4];
        uint32_t a[4];
        ldsm4t(a, a0 + ks * 1024);
        mma16816(c0[ks & 1], a, b0, b1);
        ldsm4t(a, a1 + ks * 1024);
        mma16816(c1[ks & 1], a, b0, b1);
    }
    if (t4 == 0) {
        red[hw * 32 + g] = c0[0][0] + c0[1][0];
        red[hw * 32 + 8 + g] = c0[0][2] + c0[1][2];
        red[hw * 32 + 16 + g] = c1[0][0] + c1[1][0];
        red[hw * 32 + 24 + g] = c1[0][2] + c1[1][2];
    }
    hbar();
    return (red[lane] + red[32 + lane]) + (red[64 + lane] + red[96 + lane]);
}

__device__ __forceinline__ void load_slice(uint32_t dst, const __nv_bfloat16* src, int ld, int ht) {
    const int row0 = ht >> 2, ch = ht & 3;
    uint32_t d = dst + row0 * 64 + ((ch ^ ((row0 >> 1) & 3)) << 4);
    const __nv_bfloat16* s = src + (size_t)row0 * ld + ch * 8;
#pragma unroll 4
    for (int i = 0; i < 16; i++) {
        cp_async16(d, s);
        d += 32 * 64;
        s += (size_t)32 * ld;
    }
    cp_async_commit();
}

struct Params {
    const __nv_bfloat16* x;
    const __nv_bfloat16* wq;
    const __nv_bfloat16* wo;
    const __nv_bfloat16* w_gate;
    const __nv_bfloat16* w_up;
    const __nv_bfloat16* w_down;
    const __nv_bfloat16* c;
    const __nv_bfloat16* w_mod;
    __nv_bfloat16* out;
    int three;
};

__global__ void __launch_bounds__(NTHREADS, 1)
fused_decode_kernel(const __grid_constant__ CUtensorMap map_k, const __grid_constant__ CUtensorMap map_v, const Params P) {
    extern __shared__ __align__(1024) unsigned char smem[];
    const uint32_t sb = smem_u32(smem);
    const int tid = threadIdx.x, warp = tid >> 5, lane = tid & 31;
    const int cta = blockIdx.x;

    const uint32_t bar_full = sb + SM_BAR;
    const uint32_t bar_empty = bar_full + NST * 8;
    const uint32_t bar_flf = bar_empty + NST * 8;
    const uint32_t bar_fle = bar_flf + 16;
    const uint32_t bar_w = bar_fle + 16;
    const uint32_t bar_q = bar_w + 8;
    const uint32_t bar_own = bar_q + 8;
    const uint32_t bar_done = bar_own + 8;
    const uint32_t bar_go = bar_done + 8;
    const uint32_t bar_pre = bar_go + 8;
    volatile int* tile_info = reinterpret_cast<volatile int*>(smem + SM_INFO);
    uint32_t* q_s = reinterpret_cast<uint32_t*>(smem + SM_QS);
    float* fl = reinterpret_cast<float*>(smem + SM_FL);
    const int g = lane >> 2, t4 = lane & 3, mi = lane >> 3, rr = lane & 7;

    if (warp == 9) {
        u64 pol;
        asm volatile("createpolicy.fractional.L2::evict_first.b64 %0, 1.0;" : "=l"(pol));
        auto issue = [&](int s, int tile) {
            tile_info[s] = tile;
            mbar_expect_tx(bar_full + 8 * s, STAGE_BYTES);
            const uint32_t dst = sb + SM_KV + s * STAGE_BYTES;
            tma_tile(dst, &map_k, tile * TILE, bar_full + 8 * s, pol);
            tma_tile(dst + STAGE_BYTES / 2, &map_v, tile * TILE, bar_full + 8 * s, pol);
        };
        if (lane == 0) {
            TS(0);
            if (sb & 1023) __trap();
            for (int s = 0; s < NST; s++) { mbar_init(bar_full + 8 * s, 1); mbar_init(bar_empty + 8 * s, 1); }
            mbar_init(bar_flf, NCW); mbar_init(bar_flf + 8, NCW);
            mbar_init(bar_fle, 1); mbar_init(bar_fle + 8, 1);
            mbar_init(bar_w, 1);
            mbar_init(bar_q, 1);
            mbar_init(bar_own, 1);
            mbar_init(bar_done, 1);
            mbar_init(bar_go, 4);
            mbar_init(bar_pre, 1);
            asm volatile("fence.mbarrier_init.release.cluster;" ::: "memory");
            asm volatile("fence.proxy.async.shared::cta;" ::: "memory");
            issue(0, cta);
        }
        __syncthreads();
        if (lane == 0) {
            unsigned t = cta + GRID;
            unsigned tn = cta + 2 * GRID;
            int s = 1, sl = (1 + NST - INFLIGHT) % NST;
            uint32_t phe = 1, phl = (1 >= INFLIGHT) ? 0u : 1u;
            int p = 1;
            while (t < (unsigned)NTILES) {
                unsigned tnn;
                if (p + 2 < NST) tnn = cta + (p + 2) * GRID;
                else tnn = NST * GRID + atomicAdd(&g_ctr, 1u);
                mbar_wait(bar_empty + 8 * s, phe);
                mbar_wait(bar_full + 8 * sl, phl);
                if (p < NST && p >= IF_EARLY) mbar_wait(bar_full + 8 * (p - IF_EARLY), 0);
                issue(s, (int)t);
                if (++s == NST) { s = 0; phe ^= 1; }
                if (++sl == NST) { sl = 0; phl ^= 1; }
                p++;
                t = tn; tn = tnn;
            }
            TS(3);
            const int marker = (int)(tn | 0x80000000u);
            for (int k = 0; k < NCW; k++) {
                mbar_wait(bar_empty + 8 * s, phe);
                tile_info[s] = marker;
                mbar_arrive(bar_full + 8 * s);
                if (++s == NST) { s = 0; phe ^= 1; }
            }
        }
        return;
    }

    if (warp == 8) {
        const uint32_t tag = (*reinterpret_cast<volatile unsigned*>(&g_epoch) + 1u) & 3u;
        __syncthreads();
#pragma unroll 1
        for (int h = 0; h < NHEAD; h++) {
            const int slot = h & 1;
            mbar_wait(bar_flf + 8 * slot, (h >> 1) & 1);
            const float* src = fl + slot * 4 * 132;
            const float m0 = src[128], m1 = src[132 + 128], m2 = src[264 + 128], m3 = src[396 + 128];
            const float M = fmaxf(fmaxf(m0, m1), fmaxf(m2, m3));
            const float Ms = (M == -INFINITY) ? 0.f : M;
            const float w0 = ex2((m0 - Ms) * LOG2E), w1 = ex2((m1 - Ms) * LOG2E);
            const float w2 = ex2((m2 - Ms) * LOG2E), w3 = ex2((m3 - Ms) * LOG2E);
            uint32_t* po = &g_po[((size_t)(h * 4) * GRID + cta) * 32 + lane];
#pragma unroll
            for (int j = 0; j < 4; j++) {
                const int d = j * 32 + lane;
                const float ov = (w0 * src[d] + w1 * src[132 + d]) + (w2 * src[264 + d] + w3 * src[396 + d]);
                tg_store(po + j * GRID * 32, ov, tag);
            }
            const float lv = (w0 * src[129] + w1 * src[132 + 129]) + (w2 * src[264 + 129] + w3 * src[396 + 129]);
            if (lane < 2) tg_store(&g_ph[(h * GRID + cta) * 2 + lane], lane ? lv : M, tag);
            if (h == NHEAD - 3) {
                uint32_t* pz = &g_po[((size_t)((NHEAD - 1) * 4) * GRID + cta) * 32 + lane];
#pragma unroll
                for (int j = 0; j < 4; j++) tg_store(pz + j * GRID * 32, 0.f, tag ^ 1u);
                if (lane < 2) tg_store(&g_ph[((NHEAD - 1) * GRID + cta) * 2 + lane], 0.f, tag ^ 1u);
            }
            __syncwarp();
            if (lane == 0) {
                mbar_arrive(bar_fle + 8 * slot);
                if (h == (cta >> 2)) mbar_arrive(bar_own);
                if (h == NHEAD - 2) mbar_arrive(bar_pre);
                if (h == NHEAD - 1) mbar_arrive(bar_done);
            }
        }
        if (lane == 0) TS(5);
        return;
    }

    if (warp < NCW) {
        uint32_t koff[4], voff[4];
#pragma unroll
        for (int j = 0; j < 4; j++) {
            koff[j] = (mi & 1) * 1024 + rr * 128 + ((((j << 1) | (mi >> 1)) ^ rr) << 4);
            voff[j] = STAGE_BYTES / 2 + (mi >> 1) * 1024 + rr * 128 + ((((j << 1) | (mi & 1)) ^ rr) << 4);
        }
        float o[8][4];
        float m_run = -INFINITY, l_run = 0.f;
#pragma unroll
        for (int i = 0; i < 8; i++) { o[i][0] = o[i][1] = o[i][2] = o[i][3] = 0.f; }
        uint32_t qf[8][2];
#pragma unroll
        for (int kk = 0; kk < 8; kk++) { qf[kk][0] = 0x3f803f80u; qf[kk][1] = 0x3f803f80u; }
        int cur = -1;
        int s = warp % NST;
        uint32_t ph = 0;
        __syncthreads();
        bool live = (P.three != 3);
        while (true) {
            if (live) {
                mbar_wait(bar_full + 8 * s, ph);
                const int tile = tile_info[s];
                const int head = tile < 0 ? NHEAD : (tile >> TPH_SHIFT);
                if (head != cur) {
                    while (cur < head) {
                        if (cur >= 0) {
                            const int slot = cur & 1;
                            mbar_wait(bar_fle + 8 * slot, ((cur >> 1) & 1) ^ 1);
                            float* dst = fl + (slot * 4 + warp) * 132;
                            float lt = l_run;
                            lt += __shfl_xor_sync(0xffffffffu, lt, 4);
                            lt += __shfl_xor_sync(0xffffffffu, lt, 8);
                            lt += __shfl_xor_sync(0xffffffffu, lt, 16);
                            if (lane == 0) { dst[128] = m_run; dst[129] = lt; }
#pragma unroll
                            for (int i = 0; i < 8; i++)
                                if (t4 == (i & 3)) { dst[i * 16 + g] = o[i][0]; dst[i * 16 + g + 8] = o[i][2]; }
                            __syncwarp();
                            if (lane == 0) mbar_arrive(bar_flf + 8 * slot);
                        }
#pragma unroll
                        for (int i = 0; i < 8; i++) { o[i][0] = o[i][1] = o[i][2] = o[i][3] = 0.f; }
                        m_run = -INFINITY; l_run = 0.f;
                        cur++;
                    }
                    if (tile < 0) break;
#pragma unroll
                    for (int kk = 0; kk < 8; kk++) { qf[kk][0] = q_s[cur * 64 + kk * 8 + t4]; qf[kk][1] = q_s[cur * 64 + kk * 8 + 4 + t4]; }
                }
            }
            const uint32_t st = sb + SM_KV + s * STAGE_BYTES;
            float sa[2][2][4];
#pragma unroll
            for (int a = 0; a < 2; a++)
#pragma unroll
                for (int b = 0; b < 2; b++) { sa[a][b][0] = sa[a][b][1] = sa[a][b][2] = sa[a][b][3] = 0.f; }
#pragma unroll
            for (int kk = 0; kk < 8; kk++) {
#pragma unroll
                for (int kg = 0; kg < 2; kg++) {
                    uint32_t a[4];
                    ldsm4(a, st + koff[kk & 3] + (kk >> 2) * 4096 + kg * 2048);
                    mma16816(sa[kg][kk & 1], a, qf[kk][0], qf[kk][1]);
                }
            }
            uint32_t va[8][4];
#pragma unroll
            for (int mt = 0; mt < 8; mt++) ldsm4t(va[mt], st + voff[mt & 3] + (mt >> 2) * 4096);
            const float scale = 0.08838834764831845f;
            const uint32_t r01 = pack_bf16(sa[0][0][0] + sa[0][1][0], sa[0][0][2] + sa[0][1][2]);
            const uint32_t r23 = pack_bf16(sa[1][0][0] + sa[1][1][0], sa[1][0][2] + sa[1][1][2]);
            const uint32_t s01 = pack_bf16(bf_lo(r01) * scale, bf_hi(r01) * scale);
            const uint32_t s23 = pack_bf16(bf_lo(r23) * scale, bf_hi(r23) * scale);
            const float s0 = bf_lo(s01), s1 = bf_hi(s01), s2 = bf_lo(s23), s3 = bf_hi(s23);
            float mx = fmaxf(fmaxf(s0, s1), fmaxf(s2, s3));
            mx = fmaxf(mx, __shfl_xor_sync(0xffffffffu, mx, 4));
            mx = fmaxf(mx, __shfl_xor_sync(0xffffffffu, mx, 8));
            mx = fmaxf(mx, __shfl_xor_sync(0xffffffffu, mx, 16));
            if (mx > m_run || !live) {
                const float corr = ex2((m_run - mx) * LOG2E);
                l_run *= corr;
#pragma unroll
                for (int i = 0; i < 8; i++) { o[i][0] *= corr; o[i][1] *= corr; o[i][2] *= corr; o[i][3] *= corr; }
                m_run = mx;
            }
            const float ml = m_run * LOG2E;
            const float p0 = ex2(fmaf(s0, LOG2E, -ml)), p1 = ex2(fmaf(s1, LOG2E, -ml));
            const float p2 = ex2(fmaf(s2, LOG2E, -ml)), p3 = ex2(fmaf(s3, LOG2E, -ml));
            l_run += (p0 + p1) + (p2 + p3);
            const uint32_t b0 = movm(pack_bf16(p0, p0)), b1 = movm(pack_bf16(p1, p1));
            const uint32_t b2 = movm(pack_bf16(p2, p2)), b3 = movm(pack_bf16(p3, p3));
#pragma unroll
            for (int mt = 0; mt < 8; mt++) mma16816(o[mt], va[mt], b0, b1);
#pragma unroll
            for (int mt = 0; mt < 8; mt++) ldsm4t(va[mt], st + voff[mt & 3] + (mt >> 2) * 4096 + 2048);
            __syncwarp();
            if (lane == 0 && live) mbar_arrive(bar_empty + 8 * s);
#pragma unroll
            for (int mt = 0; mt < 8; mt++) mma16816(o[mt], va[mt], b2, b3);
            if (live) {
                s += NCW;
                if (s >= NST) { s -= NST; ph ^= 1; }
            } else {
                mbar_wait(bar_q, 0);
                live = true;
            }
        }
        if (tid == 0) TS(4);
        return;
    }

    const int ht = tid - 128, hw = warp - 4;
    uint32_t* vec = reinterpret_cast<uint32_t*>(smem + SM_VEC);
    float* red = reinterpret_cast<float*>(smem + SM_RED);
    float2* stat = reinterpret_cast<float2*>(smem + SM_STAT);

    const uint2 cw = reinterpret_cast<const uint2*>(P.c)[ht];
    const uint2 xw = reinterpret_cast<const uint2*>(P.x)[ht];
    const uint32_t flag = *reinterpret_cast<volatile unsigned*>(&g_epoch) + 1u;
    if (hw == 0 && lane < 16) {
        if (cta < MOD_CTAS) ll_store(&g_mod[cta * 16 + lane], 0u, 0u);
        if (cta < Q_CTAS) ll_store(&g_q[cta * 16 + lane], 0u, 0u);
    }
    if (cta < MOD0_CTAS) load_slice(sb + SM_WGU, P.w_mod + cta * 32, 3072, ht);
    if (cta < Q_CTAS) load_slice(sb + SM_WO, P.wq + cta * 32, 4096, ht);
    const uint32_t sc0 = pack_bf16(silu_bf(bf_lo(cw.x)), silu_bf(bf_hi(cw.x)));
    const uint32_t sc1 = pack_bf16(silu_bf(bf_lo(cw.y)), silu_bf(bf_hi(cw.y)));
    *reinterpret_cast<uint2*>(vec + 2 * ht) = make_uint2(sc0, sc1);
    __syncthreads();
    if (ht == 0) TS(9);
    const float4 xv = make_float4(bf_lo(xw.x), bf_hi(xw.x), bf_lo(xw.y), bf_hi(xw.y));
    const float4 ln = layernorm512(xv, stat);
    if (ht == 0) TS(10);
    if (cta < MOD0_CTAS) {
        asm volatile("cp.async.wait_group 1;" ::: "memory");
        hbar();
        const float r = gemv512x32(sb + SM_WGU, vec, red);
        const float o2 = __shfl_xor_sync(0xffffffffu, r, 1);
        if (hw == 0 && (lane & 1) == 0) ll_store(&g_mod[cta * 16 + (lane >> 1)], pack_bf16(r, o2), flag);
    }
    asm volatile("cp.async.wait_group 0;" ::: "memory");
    __syncwarp();
    if (lane == 0) mbar_arrive(bar_go);
    if (ht == 0) TS(11);
    {
        u64 v[4] = {0, 0, 0, 0};
        unsigned spins = 0;
        while (true) {
            ll_load2(&g_mod[2 * ht], v[0], v[1]);
            ll_load2(&g_mod[256 + 2 * ht], v[2], v[3]);
            if (ll_ok(v[0], flag) && ll_ok(v[1], flag) && ll_ok(v[2], flag) && ll_ok(v[3], flag)) break;
            if (++spins > SPIN_LIMIT) __trap();
        }
        const uint32_t s0 = (uint32_t)v[0], s1 = (uint32_t)v[1], c0 = (uint32_t)v[2], c1 = (uint32_t)v[3];
        const uint32_t h0 = pack_bf16(rbf(ln.x * rbf(1.f + bf_lo(c0))) + bf_lo(s0), rbf(ln.y * rbf(1.f + bf_hi(c0))) + bf_hi(s0));
        const uint32_t h1 = pack_bf16(rbf(ln.z * rbf(1.f + bf_lo(c1))) + bf_lo(s1), rbf(ln.w * rbf(1.f + bf_hi(c1))) + bf_hi(s1));
        hbar();
        *reinterpret_cast<uint2*>(vec + 2 * ht) = make_uint2(h0, h1);
    }
    hbar();
    if (ht == 0) TS(1);
    if (cta < Q_CTAS) {
        const float r = gemv512x32(sb + SM_WO, vec, red);
        const float o2 = __shfl_xor_sync(0xffffffffu, r, 1);
        if (hw == 0 && (lane & 1) == 0) ll_store(&g_q[cta * 16 + (lane >> 1)], pack_bf16(r, o2), flag);
    }
    if (ht == 0) TS(12);
    {
        u64 v[16];
#pragma unroll
        for (int k = 0; k < 16; k++) v[k] = 0;
        unsigned spins = 0;
        while (true) {
            bool ok = true;
#pragma unroll
            for (int k = 0; k < 8; k++) ll_load2(&g_q[k * 256 + ht * 2], v[2 * k], v[2 * k + 1]);
#pragma unroll
            for (int k = 0; k < 16; k++) ok = ok && ll_ok(v[k], flag);
            if (ok) break;
            if (++spins > SPIN_LIMIT) __trap();
        }
#pragma unroll
        for (int k = 0; k < 8; k++)
            *reinterpret_cast<uint2*>(&q_s[k * 256 + ht * 2]) = make_uint2((uint32_t)v[2 * k], (uint32_t)v[2 * k + 1]);
    }
    hbar();
    if (ht == 0) { mbar_arrive(bar_q); TS(2); }
    if (cta >= Q_CTAS) return;

    if (cta >= MOD0_CTAS && cta < MOD_CTAS) {
        load_slice(sb + SM_WGU, P.w_mod + cta * 32, 3072, ht);
        *reinterpret_cast<uint2*>(vec + 2 * ht) = make_uint2(sc0, sc1);
        asm volatile("cp.async.wait_group 0;" ::: "memory");
        hbar();
        const float r = gemv512x32(sb + SM_WGU, vec, red);
        const float o2 = __shfl_xor_sync(0xffffffffu, r, 1);
        if (hw == 0 && (lane & 1) == 0) ll_store(&g_mod[cta * 16 + (lane >> 1)], pack_bf16(r, o2), flag);
    }
    hbar();
    asm volatile("fence.proxy.async.shared::cta;" ::: "memory");
    if (hw == 0) {
        if (lane == 0) mbar_expect_tx(bar_w, 32 * 1024 + (cta < FFN_CTAS ? 16 * 1024 : 0));
        __syncwarp();
        bulk_g2s(sb + SM_WO + lane * WROW, P.wo + (size_t)(cta * 32 + lane) * D_MODEL, 1024, bar_w);
        if (cta < FFN_CTAS && lane < 16)
            bulk_g2s(sb + SM_WD + lane * WROW, P.w_down + (size_t)(cta * 16 + lane) * D_MODEL, 1024, bar_w);
    }
    if (cta < FFN_CTAS) {
        const int row0 = ht >> 2, ch = ht & 3;
        uint32_t d = sb + SM_WGU + row0 * 64 + ((ch ^ ((row0 >> 1) & 3)) << 4);
        const __nv_bfloat16* s = (ch < 2 ? P.w_gate : P.w_up) + (size_t)row0 * FF + cta * 16 + (ch & 1) * 8;
#pragma unroll 4
        for (int i = 0; i < 16; i++) {
            cp_async16(d, s);
            d += 32 * 64;
            s += (size_t)32 * FF;
        }
        cp_async_commit();
    }
    uint32_t md[8];
    {
        u64 v[8];
#pragma unroll
        for (int k = 0; k < 8; k++) v[k] = 0;
        unsigned spins = 0;
        while (true) {
            bool ok = true;
#pragma unroll
            for (int k = 0; k < 4; k++) ll_load2(&g_mod[(2 + k) * 256 + 2 * ht], v[2 * k], v[2 * k + 1]);
#pragma unroll
            for (int k = 0; k < 8; k++) ok = ok && ll_ok(v[k], flag);
            if (ok) break;
            if (++spins > SPIN_LIMIT) __trap();
            __nanosleep(100);
        }
#pragma unroll
        for (int k = 0; k < 8; k++) md[k] = (uint32_t)v[k];
    }
    asm volatile("cp.async.wait_all;" ::: "memory");
    mbar_wait(bar_w, 0);
    hbar();

    const uint32_t tag = flag & 3u;
    const int h = cta >> 2, j = cta & 3;
    const bool last_unit = (h == NHEAD - 1);
    const int n0 = (hw * 8 + t4) * 16 + g;
#pragma unroll 1
    for (int pass = 0; pass < P.three; pass++) {
        const uint32_t c_live = last_unit ? (pass == 2) : (pass == 1);
        if (pass == 1 && last_unit) mbar_wait(bar_pre, 0);
        if (pass < 2 || last_unit) {
            const uint32_t live = c_live;
            uint32_t rp[4] = {0, 0, 0, 0};
            {
                const uint32_t* Rp = &g_R[(size_t)((h - 1) * 4 + j) * D_MODEL];
                const uint32_t lv = live && h > 0;
                unsigned spins = 0;
                if (ht == 0) {
                    while (true) {
                        tg_load(Rp, rp[0], lv);
                        if (!lv || (rp[0] & 3u) == tag) break;
                        if (++spins > SPIN_LIMIT) __trap();
                        __nanosleep(400);
                    }
                }
                hbar();
                while (true) {
                    tg_load(Rp + n0, rp[0], lv); tg_load(Rp + n0 + 8, rp[1], lv);
                    tg_load(Rp + n0 + 64, rp[2], lv); tg_load(Rp + n0 + 72, rp[3], lv);
                    if (!lv || tg_bad4(make_uint4(rp[0], rp[1], rp[2], rp[3]), tag) == 0) break;
                    if (++spins > SPIN_LIMIT) __trap();
                }
            }
            const int sub = lane >> 3, c8 = lane & 7;
            const uint32_t* po = &g_po[((size_t)(h * 4 + j) * GRID + 4 * sub + hw) * 32 + 4 * c8];
            const uint32_t* ph = &g_ph[(h * GRID + lane) * 2];
            uint32_t hm[5], hl[5];
            uint4 ov[9];
#pragma unroll
            for (int k = 0; k < 5; k++) { hm[k] = 0xff800000u | tag; hl[k] = tag; }
#pragma unroll
            for (int i = 0; i < 9; i++) ov[i] = make_uint4(tag, tag, tag, tag);
            if (live) mbar_wait(bar_own, 0);
            unsigned spins = 0;
            while (true) {
#pragma unroll
                for (int k = 0; k < 5; k++) tg_load2(ph + 64 * k, hm[k], hl[k], live && (k < 4 || lane < GRID - 128));
#pragma unroll
                for (int i = 0; i < 9; i++) tg_load4(po + i * 16 * 32, ov[i], live && (i < 8 || sub == 0));
                uint32_t bad = 0;
#pragma unroll
                for (int k = 0; k < 5; k++) bad |= ((hm[k] ^ tag) | (hl[k] ^ tag)) & 3u;
#pragma unroll
                for (int i = 0; i < 9; i++) bad |= tg_bad4(ov[i], tag);
                if (__all_sync(0xffffffffu, bad == 0 || !live)) break;
                if (++spins > SPIN_LIMIT) __trap();
                if (!last_unit) __nanosleep(300);
            }
            TSW(14);
            CKS(0);
            int mk = (int)0x807fffff;
#pragma unroll
            for (int k = 0; k < 5; k++) {
                const int b = (int)(hm[k] & ~3u);
                mk = max(mk, b ^ ((b >> 31) & 0x7fffffff));
            }
            mk = __reduce_max_sync(0xffffffffu, mk);
            const float M = __int_as_float(mk ^ ((mk >> 31) & 0x7fffffff));
            float wt[5], L = 0.f;
#pragma unroll
            for (int k = 0; k < 5; k++) {
                wt[k] = ex2((tg_dec(hm[k]) - M) * LOG2E);
                L = fmaf(wt[k], tg_dec(hl[k]), L);
            }
            float a0 = 0.f, a1 = 0.f, a2 = 0.f, a3 = 0.f;
#pragma unroll
            for (int i = 0; i < 9; i++) {
                const float wv = __shfl_sync(0xffffffffu, wt[i >> 1], (16 * (i & 1) + 4 * sub + hw) & 31);
                a0 = fmaf(wv, tg_dec(ov[i].x), a0); a1 = fmaf(wv, tg_dec(ov[i].y), a1);
                a2 = fmaf(wv, tg_dec(ov[i].z), a2); a3 = fmaf(wv, tg_dec(ov[i].w), a3);
            }
            a0 += __shfl_xor_sync(0xffffffffu, a0, 8); a1 += __shfl_xor_sync(0xffffffffu, a1, 8);
            a2 += __shfl_xor_sync(0xffffffffu, a2, 8); a3 += __shfl_xor_sync(0xffffffffu, a3, 8);
            a0 += __shfl_xor_sync(0xffffffffu, a0, 16); a1 += __shfl_xor_sync(0xffffffffu, a1, 16);
            a2 += __shfl_xor_sync(0xffffffffu, a2, 16); a3 += __shfl_xor_sync(0xffffffffu, a3, 16);
            if (lane < 8) *reinterpret_cast<float4*>(red + hw * 32 + 4 * lane) = make_float4(a0, a1, a2, a3);
            L = warp_sum(L);
            CKS(1);
            hbar();
            uint32_t wa[16][4];
#pragma unroll
            for (int i = 0; i < 8; i++) {
                const uint32_t base = sb + SM_WO + ((mi >> 1) * 8 + rr) * WROW + ((hw * 8 + i) * 16 + (mi & 1) * 8) * 2;
                ldsm4t(wa[2 * i], base);
                ldsm4t(wa[2 * i + 1], base + 16 * WROW);
            }
            const float of = __fdividef((red[lane] + red[32 + lane]) + (red[64 + lane] + red[96 + lane]), L);
            const uint32_t pr = pack_bf16(of, __shfl_xor_sync(0xffffffffu, of, 1));
            const uint32_t ob0 = __shfl_sync(0xffffffffu, pr, 2 * t4), ob1 = __shfl_sync(0xffffffffu, pr, 2 * t4 + 8);
            const uint32_t ob2 = __shfl_sync(0xffffffffu, pr, 2 * t4 + 16), ob3 = __shfl_sync(0xffffffffu, pr, 2 * t4 + 24);
            float y[8][4];
#pragma unroll
            for (int i = 0; i < 8; i++) {
                y[i][0] = y[i][1] = y[i][2] = y[i][3] = 0.f;
                mma16816(y[i], wa[2 * i], ob0, ob1);
            }
#pragma unroll
            for (int i = 0; i < 8; i++) mma16816(y[i], wa[2 * i + 1], ob2, ob3);
            const float ya = t4 == 0 ? y[0][0] : t4 == 1 ? y[1][0] : t4 == 2 ? y[2][0] : y[3][0];
            const float yb = t4 == 0 ? y[0][2] : t4 == 1 ? y[1][2] : t4 == 2 ? y[2][2] : y[3][2];
            const float yc = t4 == 0 ? y[4][0] : t4 == 1 ? y[5][0] : t4 == 2 ? y[6][0] : y[7][0];
            const float yd = t4 == 0 ? y[4][2] : t4 == 1 ? y[5][2] : t4 == 2 ? y[6][2] : y[7][2];
            CKS(2);
            uint32_t* Rn = &g_R[(size_t)(h * 4 + j) * D_MODEL];
            const uint32_t stag = live ? tag : (tag ^ 1u), sl = pass > 0;
            tg_store(Rn + n0, tg_dec(rp[0]) + ya, stag, sl);
            tg_store(Rn + n0 + 8, tg_dec(rp[1]) + yb, stag, sl);
            tg_store(Rn + n0 + 64, tg_dec(rp[2]) + yc, stag, sl);
            tg_store(Rn + n0 + 72, tg_dec(rp[3]) + yd, stag, sl);
            TSW(15);
        }
        if (pass == 1) mbar_wait(bar_pre, 0);
        const uint32_t live = (pass == 2);
        uint32_t ga[8][4], ua[8][4];
        {
            const int row0 = hw * 128 + (mi >> 1) * 8 + rr;
            const int sw = (row0 >> 1) & 3;
            const uint32_t a0 = sb + SM_WGU + row0 * 64 + (((mi & 1) ^ sw) << 4);
            const uint32_t a1 = sb + SM_WGU + row0 * 64 + (((2 + (mi & 1)) ^ sw) << 4);
#pragma unroll
            for (int ks = 0; ks < 8; ks++) { ldsm4t(ga[ks], a0 + ks * 1024); ldsm4t(ua[ks], a1 + ks * 1024); }
        }
        float4 x1;
        {
            uint4 v[4];
#pragma unroll
            for (int k = 0; k < 4; k++) v[k] = make_uint4(0, 0, 0, 0);
            const uint32_t* R = &g_R[(size_t)((NHEAD - 1) * 4) * D_MODEL + 4 * ht];
            if (live) mbar_wait(bar_done, 0);
            unsigned spins = 0;
            while (true) {
                uint32_t bad = 0;
#pragma unroll
                for (int k = 0; k < 4; k++) tg_load4(R + k * D_MODEL, v[k], live);
#pragma unroll
                for (int k = 0; k < 4; k++) bad |= tg_bad4(v[k], tag);
                if (__all_sync(0xffffffffu, bad == 0 || !live)) break;
                if (++spins > SPIN_LIMIT) __trap();
            }
            const float a0 = (tg_dec(v[0].x) + tg_dec(v[1].x)) + (tg_dec(v[2].x) + tg_dec(v[3].x));
            const float a1 = (tg_dec(v[0].y) + tg_dec(v[1].y)) + (tg_dec(v[2].y) + tg_dec(v[3].y));
            const float a2 = (tg_dec(v[0].z) + tg_dec(v[1].z)) + (tg_dec(v[2].z) + tg_dec(v[3].z));
            const float a3 = (tg_dec(v[0].w) + tg_dec(v[1].w)) + (tg_dec(v[2].w) + tg_dec(v[3].w));
            x1.x = rbf(bf_lo(xw.x) + rbf(bf_lo(md[0]) * rbf(a0)));
            x1.y = rbf(bf_hi(xw.x) + rbf(bf_hi(md[0]) * rbf(a1)));
            x1.z = rbf(bf_lo(xw.y) + rbf(bf_lo(md[1]) * rbf(a2)));
            x1.w = rbf(bf_hi(xw.y) + rbf(bf_hi(md[1]) * rbf(a3)));
        }
        TSW(6);
        CKS(3);
        if (cta < FFN_CTAS) {
            const float4 y = layernorm512(x1, stat);
            CKS(4);
            const uint32_t h0 = pack_bf16(rbf(y.x * rbf(1.f + bf_lo(md[4]))) + bf_lo(md[2]), rbf(y.y * rbf(1.f + bf_hi(md[4]))) + bf_hi(md[2]));
            const uint32_t h1 = pack_bf16(rbf(y.z * rbf(1.f + bf_lo(md[5]))) + bf_lo(md[3]), rbf(y.w * rbf(1.f + bf_hi(md[5]))) + bf_hi(md[3]));
            *reinterpret_cast<uint2*>(vec + 2 * ht) = make_uint2(h0, h1);
            __syncwarp();
            CKS(5);
            float c0[2][4], c1[2][4];
#pragma unroll
            for (int i = 0; i < 2; i++) { c0[i][0] = c0[i][1] = c0[i][2] = c0[i][3] = 0.f; c1[i][0] = c1[i][1] = c1[i][2] = c1[i][3] = 0.f; }
            const uint32_t* vp = vec + hw * 64 + t4;
#pragma unroll
            for (int ks = 0; ks < 8; ks++) {
                const uint32_t b0 = vp[ks * 8], b1 = vp[ks * 8 + 4];
                mma16816(c0[ks & 1], ga[ks], b0, b1);
                mma16816(c1[ks & 1], ua[ks], b0, b1);
            }
            if (t4 == 0) {
                red[hw * 32 + g] = c0[0][0] + c0[1][0];
                red[hw * 32 + 8 + g] = c0[0][2] + c0[1][2];
                red[hw * 32 + 16 + g] = c1[0][0] + c1[1][0];
                red[hw * 32 + 24 + g] = c1[0][2] + c1[1][2];
            }
            hbar();
            uint32_t da[8][4];
#pragma unroll
            for (int i = 0; i < 8; i++)
                ldsm4t(da[i], sb + SM_WD + ((mi >> 1) * 8 + rr) * WROW + ((hw * 8 + i) * 16 + (mi & 1) * 8) * 2);
            const float gx = rbf((red[lane] + red[32 + lane]) + (red[64 + lane] + red[96 + lane]));
            CKS(6);
            const float uu = __shfl_down_sync(0xffffffffu, gx, 16);
            const float inner = 0.7978845608028654f * (gx + 0.044715f * gx * gx * gx);
            const float ge = rbf(__fdividef(gx, 1.f + ex2(-2.f * LOG2E * inner)));
            const float act = rbf(ge * uu);
            const uint32_t ap = pack_bf16(act, __shfl_xor_sync(0xffffffffu, act, 1));
            const uint32_t ab0 = __shfl_sync(0xffffffffu, ap, 2 * t4), ab1 = __shfl_sync(0xffffffffu, ap, 2 * t4 + 8);
            CKS(7);
            float f[8][4];
#pragma unroll
            for (int i = 0; i < 8; i++) {
                f[i][0] = f[i][1] = f[i][2] = f[i][3] = 0.f;
                mma16816(f[i], da[i], ab0, ab1);
            }
            const float fa = t4 == 0 ? f[0][0] : t4 == 1 ? f[1][0] : t4 == 2 ? f[2][0] : f[3][0];
            const float fb = t4 == 0 ? f[0][2] : t4 == 1 ? f[1][2] : t4 == 2 ? f[2][2] : f[3][2];
            const float fc = t4 == 0 ? f[4][0] : t4 == 1 ? f[5][0] : t4 == 2 ? f[6][0] : f[7][0];
            const float fd = t4 == 0 ? f[4][2] : t4 == 1 ? f[5][2] : t4 == 2 ? f[6][2] : f[7][2];
            CKS(8);
            uint32_t* fo = &g_f[(size_t)cta * D_MODEL + (hw * 8 + t4) * 16 + g];
            const uint32_t stag = live ? tag : (tag ^ 1u), sl = pass > 0;
            tg_store(fo, fa, stag, sl);
            tg_store(fo + 8, fb, stag, sl);
            tg_store(fo + 64, fc, stag, sl);
            tg_store(fo + 72, fd, stag, sl);
        }
        TSW(7);
        CKS(9);
        if (hw == (cta >> 5)) {
            uint4 v[4];
#pragma unroll
            for (int k = 0; k < 4; k++) v[k] = make_uint4(tag, tag, tag, tag);
            const uint32_t* src = &g_f[(size_t)lane * D_MODEL + cta * 4];
            unsigned spins = 0;
            while (true) {
                uint32_t bad = 0;
#pragma unroll
                for (int k = 0; k < 4; k++) tg_load4(src + k * 32 * D_MODEL, v[k], live && (k < 3 || lane < FFN_CTAS - 96));
#pragma unroll
                for (int k = 0; k < 4; k++) bad |= tg_bad4(v[k], tag);
                if (__all_sync(0xffffffffu, bad == 0 || !live)) break;
                if (++spins > SPIN_LIMIT) __trap();
            }
            float s0 = (tg_dec(v[0].x) + tg_dec(v[1].x)) + (tg_dec(v[2].x) + tg_dec(v[3].x));
            float s1 = (tg_dec(v[0].y) + tg_dec(v[1].y)) + (tg_dec(v[2].y) + tg_dec(v[3].y));
            float s2 = (tg_dec(v[0].z) + tg_dec(v[1].z)) + (tg_dec(v[2].z) + tg_dec(v[3].z));
            float s3 = (tg_dec(v[0].w) + tg_dec(v[1].w)) + (tg_dec(v[2].w) + tg_dec(v[3].w));
#pragma unroll
            for (int o2 = 1; o2 < 32; o2 <<= 1) {
                s0 += __shfl_xor_sync(0xffffffffu, s0, o2);
                s1 += __shfl_xor_sync(0xffffffffu, s1, o2);
                s2 += __shfl_xor_sync(0xffffffffu, s2, o2);
                s3 += __shfl_xor_sync(0xffffffffu, s3, o2);
            }
            if (ht == cta) {
                const uint32_t o0 = pack_bf16(x1.x + rbf(bf_lo(md[6]) * rbf(s0)), x1.y + rbf(bf_hi(md[6]) * rbf(s1)));
                const uint32_t o1 = pack_bf16(x1.z + rbf(bf_lo(md[7]) * rbf(s2)), x1.w + rbf(bf_hi(md[7]) * rbf(s3)));
                if (live) {
                    *reinterpret_cast<uint2*>(P.out + 4 * cta) = make_uint2(o0, o1);
                    if (cta == 0) {
                        g_ctr = 0;
                        g_epoch = flag;
                    }
                }
            }
        }
        if (pass < 2) hbar();
    }
}

typedef CUresult (*EncodeTiledFn)(CUtensorMap*, CUtensorMapDataType, cuuint32_t, void*, const cuuint64_t*, const cuuint64_t*,
                                  const cuuint32_t*, const cuuint32_t*, CUtensorMapInterleave, CUtensorMapSwizzle,
                                  CUtensorMapL2promotion, CUtensorMapFloatOOBfill);

bool make_kv_map(EncodeTiledFn enc, CUtensorMap* m, void* base) {
    cuuint64_t gd[3] = {64, (cuuint64_t)NHEAD * SEQ, 2};
    cuuint64_t gs[2] = {256, 128};
    cuuint32_t bd[3] = {64, TILE, 2};
    cuuint32_t es[3] = {1, 1, 1};
    return enc(m, CU_TENSOR_MAP_DATA_TYPE_BFLOAT16, 3, base, gd, gs, bd, es, CU_TENSOR_MAP_INTERLEAVE_NONE,
               CU_TENSOR_MAP_SWIZZLE_128B, CU_TENSOR_MAP_L2_PROMOTION_L2_256B, CU_TENSOR_MAP_FLOAT_OOB_FILL_NONE) == CUDA_SUCCESS;
}

}

extern "C" void kernel_launch(void* const* d_in, const int* in_sizes, int n_in, void* d_out, int out_size) {
    (void)in_sizes; (void)n_in; (void)out_size;
    static EncodeTiledFn enc = nullptr;
    static CUtensorMap map_k, map_v;
    static void *k_ptr = nullptr, *v_ptr = nullptr;
    if (!enc) {
        void* fn = nullptr;
        cudaDriverEntryPointQueryResult qr;
        if (cudaGetDriverEntryPoint("cuTensorMapEncodeTiled", &fn, cudaEnableDefault, &qr) != cudaSuccess || !fn) {
            fprintf(stderr, "cuTensorMapEncodeTiled not available\n");
            return;
        }
        enc = (EncodeTiledFn)fn;
        cudaFuncSetAttribute(fused_decode_kernel, cudaFuncAttributeMaxDynamicSharedMemorySize, SM_TOTAL);
    }
    if (k_ptr != d_in[1] || v_ptr != d_in[2]) {
        if (!make_kv_map(enc, &map_k, d_in[1]) || !make_kv_map(enc, &map_v, d_in[2])) {
            fprintf(stderr, "tensor map encode failed\n");
            return;
        }
        k_ptr = d_in[1];
        v_ptr = d_in[2];
    }
    Params P;
    P.x = (const __nv_bfloat16*)d_in[0];
    P.wq = (const __nv_bfloat16*)d_in[3];
    P.wo = (const __nv_bfloat16*)d_in[4];
    P.w_gate = (const __nv_bfloat16*)d_in[6];
    P.w_up = (const __nv_bfloat16*)d_in[7];
    P.w_down = (const __nv_bfloat16*)d_in[8];
    P.c = (const __nv_bfloat16*)d_in[9];
    P.w_mod = (const __nv_bfloat16*)d_in[10];
    P.out = (__nv_bfloat16*)d_out;
    P.three = 3;
    fused_decode_kernel<<<GRID, NTHREADS, SM_TOTAL, cudaStreamPerThread>>>(map_k, map_v, P);
}
```

```cpp
#include <cuda_runtime.h>
#include <cuda_bf16.h>
#include <cuda.h>
#include <stdint.h>
#include <stdio.h>

namespace {

typedef unsigned long long u64;

constexpr int D_MODEL = 512;
constexpr int NHEAD = 32;
constexpr int SEQ = 65536;
constexpr int DH = 128;
constexpr int FF = 1792;
constexpr int GRID = 132;

constexpr int TILE = 32;
constexpr int TPH = SEQ / TILE;
constexpr int TPH_SHIFT = 11;
constexpr int NTILES = NHEAD * TPH;
#define NST 8
#define EARLY_GATE 0
#define IF_EARLY 2
#define INFLIGHT 3
constexpr int STAGE_BYTES = TILE * DH * 2 * 2;
constexpr int NCW = 4;
constexpr int NTHREADS = 320;

constexpr int MOD0_CTAS = 32;
constexpr int MOD_CTAS = 96;
constexpr int Q_CTAS = 128;
constexpr int FFN_CTAS = 112;

#define RREP 1

constexpr int WROW = 1040;
constexpr int SM_KV = 0;
constexpr int SM_WO = SM_KV + NST * STAGE_BYTES;
constexpr int SM_WD = SM_WO + 32 * WROW;
constexpr int SM_WGU = SM_WD + 16 * WROW;
constexpr int SM_QS = SM_WGU + 512 * 64;
constexpr int SM_FL = SM_QS + 8192;
constexpr int SM_VEC = SM_FL + 2 * 4 * 132 * 4;
constexpr int SM_RED = SM_VEC + 1024;
constexpr int SM_STAT = SM_RED + 512;
constexpr int SM_FIN = SM_STAT + 64;
constexpr int SM_BAR = SM_FIN + 64;
constexpr int SM_INFO = SM_BAR + (2 * NST + 13) * 8;
constexpr int SM_TOTAL = SM_INFO + NST * 4;
static_assert(SM_TOTAL <= 232448, "shared memory budget");
static_assert(SM_BAR % 8 == 0 && SM_STAT % 16 == 0, "alignment");

__device__ unsigned g_epoch;
__device__ unsigned g_ctr;
__device__ __align__(128) u64 g_mod[1536];
__device__ __align__(128) u64 g_q[2048];
__device__ __align__(128) uint32_t g_po[NHEAD * 4 * GRID * 32];
__device__ __align__(128) uint32_t g_ph[NHEAD * GRID * 2];
__device__ __align__(128) uint32_t g_R[(NHEAD - 1 + RREP) * 4 * D_MODEL];
__device__ __align__(128) uint32_t g_W[16 * 8 * 32];
__device__ __align__(128) uint32_t g_f[128 * FFN_CTAS * 4];
#define TS(i) do { } while (0)
#define CKS(i) do { } while (0)
#define TSW(i) do { } while (0)

constexpr float LOG2E = 1.4426950408889634f;
constexpr unsigned SPIN_LIMIT = 1u << 24;
#define WAIT_HINT_NS 20000u
#define COMBINE_DELAY_NS 4000
#define PO_RING 32
#define EARLY_BG 0
#define MODGATE 0
#define WQ_LATE 0
#define PRO_WAITQ 1
#define PFW 0
#define AHEAD 1
#define DEFER 1
#define PF 0
#define WL_ROUNDS 2
#define WL_WIN 0
#define WL_K 2
#define TIMED 1
#define R_DELAY_NS 580
#define F_DELAY_NS 160
#define F_DELAY2_NS 1250
constexpr int WREP = 8;
#define POLL_GAP 150
#define RPOLL_NS 400

#define CPPF_A ""
#define CPPF_B ".L2::256B"
__device__ __forceinline__ uint32_t smem_u32(const void* p) { return (uint32_t)__cvta_generic_to_shared(p); }
__device__ __forceinline__ void mbar_init(uint32_t bar, uint32_t cnt) {
    asm volatile("mbarrier.init.shared::cta.b64 [%0], %1;" ::"r"(bar), "r"(cnt) : "memory");
}
__device__ __forceinline__ void mbar_expect_tx(uint32_t bar, uint32_t bytes) {
    asm volatile("mbarrier.arrive.expect_tx.shared::cta.b64 _, [%0], %1;" ::"r"(bar), "r"(bytes) : "memory");
}
__device__ __forceinline__ void mbar_arrive(uint32_t bar) {
    asm volatile("mbarrier.arrive.shared::cta.b64 _, [%0];" ::"r"(bar) : "memory");
}
__device__ __forceinline__ void mbar_wait(uint32_t bar, uint32_t parity) {
    unsigned spins = 0;
    while (true) {
        uint32_t ok;
        asm volatile(
            "{\n.reg .pred p;\n"
            "mbarrier.try_wait.parity.shared::cta.b64 p, [%1], %2;\n"
            "selp.u32 %0, 1, 0, p;\n}"
            : "=r"(ok)
            : "r"(bar), "r"(parity)
            : "memory");
        if (ok) break;
        if (++spins > SPIN_LIMIT) __trap();
    }
}
__device__ __forceinline__ void mbar_wait_long(uint32_t bar, uint32_t parity) {
    unsigned spins = 0;
    while (true) {
        uint32_t ok;
        asm volatile(
            "{\n.reg .pred p;\n"
            "mbarrier.try_wait.parity.shared::cta.b64 p, [%1], %2, %3;\n"
            "selp.u32 %0, 1, 0, p;\n}"
            : "=r"(ok)
            : "r"(bar), "r"(parity), "r"(WAIT_HINT_NS)
            : "memory");
        if (ok) break;
        if (++spins > SPIN_LIMIT) __trap();
    }
}
__device__ __forceinline__ void spin_cycles(uint32_t n) {
    uint32_t t0, t;
    asm volatile("mov.u32 %0, %%clock;" : "=r"(t0)::"memory");
    do { asm volatile("mov.u32 %0, %%clock;" : "=r"(t)::"memory"); } while (t - t0 < n);
}
__device__ __forceinline__ uint32_t gtime32() {
    uint32_t t;
    asm volatile("mov.u32 %0, %%globaltimer_lo;" : "=r"(t)::"memory");
    return t;
}
__device__ __forceinline__ void spin_until(uint32_t t) {
    unsigned n = 0;
    while ((int)(gtime32() - t) < 0 && ++n < 256u) { }
}
__device__ __forceinline__ void bar_sync(int id, int n) { asm volatile("bar.sync %0, %1;" ::"r"(id), "r"(n) : "memory"); }
__device__ __forceinline__ void hbar() { asm volatile("bar.sync 1, 128;" ::: "memory"); }

__device__ __forceinline__ void tma_tile(uint32_t dst, const CUtensorMap* m, int key, uint32_t bar, u64 pol) {
    asm volatile(
        "cp.async.bulk.tensor.3d.shared::cluster.global.mbarrier::complete_tx::bytes.L2::cache_hint "
        "[%0], [%1, {%3, %4, %3}], [%2], %5;"
        ::"r"(dst), "l"(m), "r"(bar), "r"(0), "r"(key), "l"(pol)
        : "memory");
}
__device__ __forceinline__ void bulk_g2s(uint32_t dst, const void* src, uint32_t bytes, uint32_t bar) {
    asm volatile("cp.async.bulk.shared::cluster.global.mbarrier::complete_tx::bytes [%0], [%1], %2, [%3];"
                 ::"r"(dst), "l"(src), "r"(bytes), "r"(bar) : "memory");
}
__device__ __forceinline__ void cp_async16(uint32_t dst, const void* src) {
    asm volatile("cp.async.cg.shared.global" CPPF_A " [%0], [%1], 16;" ::"r"(dst), "l"(src) : "memory");
}
__device__ __forceinline__ void cp_async16_p(uint32_t dst, const void* src, uint32_t live) {
    asm volatile("{\n.reg .pred p;\nsetp.ne.u32 p, %2, 0;\n@p cp.async.cg.shared.global" CPPF_B " [%0], [%1], 16;\n}" ::"r"(dst), "l"(src), "r"(live) : "memory");
}
__device__ __forceinline__ void bulk_g2s_p(uint32_t dst, const void* src, uint32_t bytes, uint32_t bar, uint32_t live) {
    asm volatile("{\n.reg .pred p;\nsetp.ne.u32 p, %4, 0;\n@p cp.async.bulk.shared::cluster.global.mbarrier::complete_tx::bytes [%0], [%1], %2, [%3];\n}"
                 ::"r"(dst), "l"(src), "r"(bytes), "r"(bar), "r"(live) : "memory");
}
__device__ __forceinline__ void mbar_expect_tx_p(uint32_t bar, uint32_t bytes, uint32_t live) {
    asm volatile("{\n.reg .pred p;\nsetp.ne.u32 p, %2, 0;\n@p mbarrier.arrive.expect_tx.shared::cta.b64 _, [%0], %1;\n}" ::"r"(bar), "r"(bytes), "r"(live) : "memory");
}
__device__ __forceinline__ void cp_async_commit() { asm volatile("cp.async.commit_group;" ::: "memory"); }
__device__ __forceinline__ void ll_store(u64* p, uint32_t data, uint32_t flag, uint32_t live = 1) {
    u64 v = ((u64)flag << 32) | data;
    asm volatile("{\n.reg .pred p;\nsetp.ne.u32 p, %2, 0;\n@p st.relaxed.gpu.global.u64 [%0], %1;\n}" ::"l"(p), "l"(v), "r"(live) : "memory");
}
__device__ __forceinline__ void ll_load(const u64* p, u64& a, uint32_t live = 1) {
    asm volatile("{\n.reg .pred p;\nsetp.ne.u32 p, %2, 0;\n@p ld.relaxed.gpu.global.u64 %0, [%1];\n}" : "+l"(a) : "l"(p), "r"(live) : "memory");
}
__device__ __forceinline__ void ll_load2(const u64* p, u64& a, u64& b, uint32_t live = 1) {
    asm volatile("{\n.reg .pred p;\nsetp.ne.u32 p, %3, 0;\n@p ld.relaxed.gpu.global.v2.u64 {%0,%1}, [%2];\n}"
                 : "+l"(a), "+l"(b) : "l"(p), "r"(live) : "memory");
}
__device__ __forceinline__ uint32_t tg_enc(float v, uint32_t tag) { return (__float_as_uint(v) & ~3u) | tag; }
__device__ __forceinline__ float tg_dec(uint32_t v) { return __uint_as_float(v & ~3u); }
__device__ __forceinline__ float tg_val(uint32_t v) { return __uint_as_float(v); }
__device__ __forceinline__ void tg_store(uint32_t* p, float v, uint32_t tag, uint32_t live = 1) {
    asm volatile("{\n.reg .pred p;\nsetp.ne.u32 p, %2, 0;\n@p st.relaxed.gpu.global.u32 [%0], %1;\n}" ::"l"(p), "r"(tg_enc(v, tag)), "r"(live) : "memory");
}
__device__ __forceinline__ void tg_store4(uint32_t* p, float a, float b, float c, float d, uint32_t tag, uint32_t live) {
    asm volatile("{\n.reg .pred p;\nsetp.ne.u32 p, %5, 0;\n@p st.relaxed.gpu.global.v4.u32 [%0], {%1,%2,%3,%4};\n}"
                 ::"l"(p), "r"(tg_enc(a, tag)), "r"(tg_enc(b, tag)), "r"(tg_enc(c, tag)), "r"(tg_enc(d, tag)), "r"(live) : "memory");
}
__device__ __forceinline__ void tg_load(const uint32_t* p, uint32_t& a, uint32_t live) {
    asm volatile("{\n.reg .pred p;\nsetp.ne.u32 p, %2, 0;\n@p ld.relaxed.gpu.global.u32 %0, [%1];\n}" : "+r"(a) : "l"(p), "r"(live) : "memory");
}
__device__ __forceinline__ void tg_load2(const uint32_t* p, uint32_t& a, uint32_t& b, uint32_t live) {
    asm volatile("{\n.reg .pred p;\nsetp.ne.u32 p, %3, 0;\n@p ld.relaxed.gpu.global.v2.u32 {%0,%1}, [%2];\n}"
                 : "+r"(a), "+r"(b) : "l"(p), "r"(live) : "memory");
}
__device__ __forceinline__ void tg_load4(const uint32_t* p, uint4& v, uint32_t live) {
    asm volatile("{\n.reg .pred p;\nsetp.ne.u32 p, %5, 0;\n@p ld.relaxed.gpu.global.v4.u32 {%0,%1,%2,%3}, [%4];\n}"
                 : "+r"(v.x), "+r"(v.y), "+r"(v.z), "+r"(v.w) : "l"(p), "r"(live) : "memory");
}
__device__ __forceinline__ uint32_t tg_bad4(const uint4& v, uint32_t tag) { return ((v.x ^ tag) | (v.y ^ tag) | (v.z ^ tag) | (v.w ^ tag)) & 3u; }
__device__ __forceinline__ bool ll_ok(u64 v, uint32_t flag) { return (uint32_t)(v >> 32) == flag; }

__device__ __forceinline__ void ldsm4(uint32_t (&r)[4], uint32_t addr) {
    asm volatile("ldmatrix.sync.aligned.m8n8.x4.shared.b16 {%0,%1,%2,%3}, [%4];"
                 : "=r"(r[0]), "=r"(r[1]), "=r"(r[2]), "=r"(r[3]) : "r"(addr) : "memory");
}
__device__ __forceinline__ void ldsm4t(uint32_t (&r)[4], uint32_t addr) {
    asm volatile("ldmatrix.sync.aligned.m8n8.x4.trans.shared.b16 {%0,%1,%2,%3}, [%4];"
                 : "=r"(r[0]), "=r"(r[1]), "=r"(r[2]), "=r"(r[3]) : "r"(addr) : "memory");
}
__device__ __forceinline__ void mma16816(float (&d)[4], const uint32_t (&a)[4], uint32_t b0, uint32_t b1) {
    asm volatile(
        "mma.sync.aligned.m16n8k16.row.col.f32.bf16.bf16.f32 {%0,%1,%2,%3}, {%4,%5,%6,%7}, {%8,%9}, {%0,%1,%2,%3};"
        : "+f"(d[0]), "+f"(d[1]), "+f"(d[2]), "+f"(d[3])
        : "r"(a[0]), "r"(a[1]), "r"(a[2]), "r"(a[3]), "r"(b0), "r"(b1));
}
__device__ __forceinline__ uint32_t movm(uint32_t a) {
    uint32_t d;
    asm volatile("movmatrix.sync.aligned.m8n8.trans.b16 %0, %1;" : "=r"(d) : "r"(a));
    return d;
}
__device__ __forceinline__ uint32_t pack_bf16(float lo, float hi) {
    uint32_t d;
    asm("cvt.rn.bf16x2.f32 %0, %1, %2;" : "=r"(d) : "f"(hi), "f"(lo));
    return d;
}
__device__ __forceinline__ float bf_lo(uint32_t v) { return __uint_as_float(v << 16); }
__device__ __forceinline__ float bf_hi(uint32_t v) { return __uint_as_float(v & 0xffff0000u); }
__device__ __forceinline__ float rbf(float x) { return bf_lo(pack_bf16(x, x)); }
__device__ __forceinline__ float ex2(float x) {
    float y;
    asm("ex2.approx.ftz.f32 %0, %1;" : "=f"(y) : "f"(x));
    return y;
}
__device__ __forceinline__ float silu_bf(float c) { return rbf(__fdividef(c, 1.f + __expf(-c))); }
__device__ __forceinline__ float warp_sum(float v) {
#pragma unroll
    for (int o = 16; o > 0; o >>= 1) v += __shfl_xor_sync(0xffffffffu, v, o);
    return v;
}
__device__ __forceinline__ float warp_max(float v) {
#pragma unroll
    for (int o = 16; o > 0; o >>= 1) v = fmaxf(v, __shfl_xor_sync(0xffffffffu, v, o));
    return v;
}

__device__ __forceinline__ float4 layernorm512(float4 x, float2* stat) {
    const int tid = threadIdx.x;
    float m = ((x.x + x.y) + (x.z + x.w)) * 0.25f;
    const float d0 = x.x - m, d1 = x.y - m, d2 = x.z - m, d3 = x.w - m;
    float q = (d0 * d0 + d1 * d1) + (d2 * d2 + d3 * d3);
#pragma unroll
    for (int r = 0; r < 5; r++) {
        const float mo = __shfl_xor_sync(0xffffffffu, m, 16 >> r);
        const float qo = __shfl_xor_sync(0xffffffffu, q, 16 >> r);
        const float dl = mo - m;
        m = fmaf(dl, 0.5f, m);
        q = fmaf(dl * dl, (float)(2 << r), q + qo);
    }
    if ((tid & 31) == 0) stat[(tid >> 5) & 3] = make_float2(m, q);
    hbar();
    const float4 s01 = *reinterpret_cast<const float4*>(stat), s23 = *reinterpret_cast<const float4*>(stat + 2);
    const float da = s01.z - s01.x, db = s23.z - s23.x;
    const float ma = fmaf(da, 0.5f, s01.x), mb = fmaf(db, 0.5f, s23.x);
    const float qa = fmaf(da * da, 64.f, s01.y + s01.w), qb = fmaf(db * db, 64.f, s23.y + s23.w);
    const float dc = mb - ma;
    const float mean = rbf(fmaf(dc, 0.5f, ma));
    const float var = rbf(fmaf(dc * dc, 128.f, qa + qb) * (1.f / 512.f));
    float den;
    asm("sqrt.approx.f32 %0, %1;" : "=f"(den) : "f"(rbf(var + 1e-5f)));
    den = rbf(den);
    float4 y;
    y.x = rbf(__fdividef(rbf(x.x - mean), den));
    y.y = rbf(__fdividef(rbf(x.y - mean), den));
    y.z = rbf(__fdividef(rbf(x.z - mean), den));
    y.w = rbf(__fdividef(rbf(x.w - mean), den));
    return y;
}

__device__ __noinline__ float gemv512x32(uint32_t wbase, const uint32_t* vec, float* red) {
    const int lane = threadIdx.x & 31, hw = (threadIdx.x >> 5) & 3;
    const int g = lane >> 2, t4 = lane & 3, mi = lane >> 3, rr = lane & 7;
    float c0[2][4], c1[2][4];
#pragma unroll
    for (int i = 0; i < 2; i++) { c0[i][0] = c0[i][1] = c0[i][2] = c0[i][3] = 0.f; c1[i][0] = c1[i][1] = c1[i][2] = c1[i][3] = 0.f; }
    const int row0 = hw * 128 + (mi >> 1) * 8 + rr;
    const int sw = (row0 >> 1) & 3;
    const uint32_t a0 = wbase + row0 * 64 + (((mi & 1) ^ sw) << 4);
    const uint32_t a1 = wbase + row0 * 64 + (((2 + (mi & 1)) ^ sw) << 4);
    const uint32_t* vp = vec + hw * 64 + t4;
#pragma unroll
    for (int ks = 0; ks < 8; ks++) {
        const uint32_t b0 = vp[ks * 8], b1 = vp[ks * 8 + 4];
        uint32_t a[4];
        ldsm4t(a, a0 + ks * 1024);
        mma16816(c0[ks & 1], a, b0, b1);
        ldsm4t(a, a1 + ks * 1024);
        mma16816(c1[ks & 1], a, b0, b1);
    }
    if (t4 == 0) {
        red[hw * 32 + g] = c0[0][0] + c0[1][0];
        red[hw * 32 + 8 + g] = c0[0][2] + c0[1][2];
        red[hw * 32 + 16 + g] = c1[0][0] + c1[1][0];
        red[hw * 32 + 24 + g] = c1[0][2] + c1[1][2];
    }
    hbar();
    return (red[lane] + red[32 + lane]) + (red[64 + lane] + red[96 + lane]);
}

__device__ __forceinline__ void load_slice(uint32_t dst, const __nv_bfloat16* src, int ld, int ht) {
    const int row0 = ht >> 2, ch = ht & 3;
    uint32_t d = dst + row0 * 64 + ((ch ^ ((row0 >> 1) & 3)) << 4);
    const __nv_bfloat16* s = src + (size_t)row0 * ld + ch * 8;
#pragma unroll 4
    for (int i = 0; i < 16; i++) {
        cp_async16(d, s);
        d += 32 * 64;
        s += (size_t)32 * ld;
    }
    cp_async_commit();
}

struct Params {
    const __nv_bfloat16* x;
    const __nv_bfloat16* wq;
    const __nv_bfloat16* wo;
    const __nv_bfloat16* w_gate;
    const __nv_bfloat16* w_up;
    const __nv_bfloat16* w_down;
    const __nv_bfloat16* c;
    const __nv_bfloat16* w_mod;
    __nv_bfloat16* out;
    int three;
};

__global__ void __launch_bounds__(NTHREADS, 1)
fused_decode_kernel(const __grid_constant__ CUtensorMap map_k, const __grid_constant__ CUtensorMap map_v, const Params P) {
    extern __shared__ __align__(1024) unsigned char smem[];
    const uint32_t sb = smem_u32(smem);
    const int tid = threadIdx.x, warp = tid >> 5, lane = tid & 31;
    const int cta = blockIdx.x;

    const uint32_t bar_full = sb + SM_BAR;
    const uint32_t bar_empty = bar_full + NST * 8;
    const uint32_t bar_flf = bar_empty + NST * 8;
    const uint32_t bar_fle = bar_flf + 16;
    const uint32_t bar_w = bar_fle + 16;
    const uint32_t bar_q = bar_w + 8;
    const uint32_t bar_own = bar_q + 8;
    const uint32_t bar_done = bar_own + 8;
    const uint32_t bar_go = bar_done + 8;
    const uint32_t bar_pre = bar_go + 8;
    const uint32_t bar_wl = bar_pre + 8;
    const uint32_t bar_w2 = bar_wl + 8;
    const uint32_t bar_q2 = bar_w2 + 8;
    volatile int* tile_info = reinterpret_cast<volatile int*>(smem + SM_INFO);
    uint32_t* q_s = reinterpret_cast<uint32_t*>(smem + SM_QS);
    float* fl = reinterpret_cast<float*>(smem + SM_FL);
    const int g = lane >> 2, t4 = lane & 3, mi = lane >> 3, rr = lane & 7;

    if (warp == 9) {
        u64 pol;
        asm volatile("createpolicy.fractional.L2::evict_first.b64 %0, 1.0;" : "=l"(pol));
        auto issue = [&](int s, int tile) {
            tile_info[s] = tile;
            mbar_expect_tx(bar_full + 8 * s, STAGE_BYTES);
            const uint32_t dst = sb + SM_KV + s * STAGE_BYTES;
            tma_tile(dst, &map_k, tile * TILE, bar_full + 8 * s, pol);
            tma_tile(dst + STAGE_BYTES / 2, &map_v, tile * TILE, bar_full + 8 * s, pol);
        };
        if (lane == 0) {
            TS(0);
            if (sb & 1023) __trap();
            for (int s = 0; s < NST; s++) { mbar_init(bar_full + 8 * s, 1); mbar_init(bar_empty + 8 * s, 1); }
            mbar_init(bar_flf, NCW); mbar_init(bar_flf + 8, NCW);
            mbar_init(bar_fle, 1); mbar_init(bar_fle + 8, 1);
            mbar_init(bar_w, 1);
            mbar_init(bar_q, 1);
            mbar_init(bar_own, 1);
            mbar_init(bar_done, 1);
            mbar_init(bar_go, 4);
            mbar_init(bar_pre, 1);
            mbar_init(bar_wl, 1);
            mbar_init(bar_w2, 1);
            mbar_init(bar_q2, 1);
            asm volatile("fence.mbarrier_init.release.cluster;" ::: "memory");
            asm volatile("fence.proxy.async.shared::cta;" ::: "memory");
            if (!MODGATE || cta >= MOD0_CTAS) issue(0, cta);
        }
        __syncthreads();
        if (tid == 9 * 32) {
            if (MODGATE && cta < MOD0_CTAS) { mbar_wait(bar_go, 0); issue(0, cta); }
            unsigned a0 = cta + GRID, a1 = cta + 2 * GRID;
            int s = 1, sl = (1 + NST - INFLIGHT) % NST;
            uint32_t phe = 1, phl = (1 >= INFLIGHT) ? 0u : 1u;
            int p = 1;
            auto step = [&](unsigned& a) -> bool {
                const unsigned t = p >= NST ? a + NST * GRID : a;
                if (t >= (unsigned)NTILES) return false;
                mbar_wait(bar_empty + 8 * s, phe);
                mbar_wait(bar_full + 8 * sl, phl);
                if (p < NST && p >= IF_EARLY) mbar_wait(bar_full + 8 * (p - IF_EARLY), 0);
                issue(s, (int)t);
                if (p + AHEAD < NST) a = cta + (p + AHEAD) * GRID;
                else asm volatile("atom.relaxed.gpu.global.add.u32 %0, [%1], 1;" : "=r"(a) : "l"(&g_ctr) : "memory");
                if (++s == NST) { s = 0; phe ^= 1; }
                if (++sl == NST) { sl = 0; phl ^= 1; }
                p++;
                return true;
            };
            while (true) {
                if (!step(a0)) break;
                if (AHEAD == 2 && !step(a1)) break;
            }
            TS(3);
            const int marker = (int)((a0 + a1) | 0x80000000u);
            for (int k = 0; k < NCW; k++) {
                mbar_wait(bar_empty + 8 * s, phe);
                tile_info[s] = marker;
                mbar_arrive(bar_full + 8 * s);
                if (++s == NST) { s = 0; phe ^= 1; }
            }
            const int ql = p - 1 - WL_K;
            mbar_wait(bar_full + 8 * (ql % NST), (ql / NST) & 1);
            mbar_arrive(bar_wl);
            TS(13);
        }
        return;
    }

    if (warp == 8) {
        const uint32_t tag = (*reinterpret_cast<volatile unsigned*>(&g_epoch) + 1u) & 3u;
        __syncthreads();
#pragma unroll 1
        for (int h = 0; h < NHEAD; h++) {
            const int slot = h & 1;
            mbar_wait_long(bar_flf + 8 * slot, (h >> 1) & 1);
            const float* src = fl + slot * 4 * 132;
            const float m0 = src[128], m1 = src[132 + 128], m2 = src[264 + 128], m3 = src[396 + 128];
            const float M = fmaxf(fmaxf(m0, m1), fmaxf(m2, m3));
            const float Ms = (M == -INFINITY) ? 0.f : M;
            const float w0 = ex2((m0 - Ms) * LOG2E), w1 = ex2((m1 - Ms) * LOG2E);
            const float w2 = ex2((m2 - Ms) * LOG2E), w3 = ex2((m3 - Ms) * LOG2E);
            uint32_t* po = &g_po[((size_t)((h % PO_RING) * 4) * GRID + cta) * 32 + lane];
#pragma unroll
            for (int j = 0; j < 4; j++) {
                const int d = j * 32 + lane;
                const float ov = (w0 * src[d] + w1 * src[132 + d]) + (w2 * src[264 + d] + w3 * src[396 + d]);
                tg_store(po + j * GRID * 32, ov, PO_RING == 32 ? tag : (((h / PO_RING) + 1) & 3));
            }
            const float lv = (w0 * src[129] + w1 * src[132 + 129]) + (w2 * src[264 + 129] + w3 * src[396 + 129]);
            if (lane < 2) tg_store(&g_ph[(h * GRID + cta) * 2 + lane], lane ? lv : M, tag);
            if (h == NHEAD - 3) {
                uint32_t* pz = &g_po[((size_t)((NHEAD - 1) * 4) * GRID + cta) * 32 + lane];
                if (PO_RING == 32)
#pragma unroll
                for (int j = 0; j < 4; j++) tg_store(pz + j * GRID * 32, 0.f, tag ^ 1u);
                if (lane < 2) tg_store(&g_ph[((NHEAD - 1) * GRID + cta) * 2 + lane], 0.f, tag ^ 1u);
            }
            __syncwarp();
            if (lane == 0) {
                mbar_arrive(bar_fle + 8 * slot);
                if (h == (cta >> 2)) mbar_arrive(bar_own);
                if (h == NHEAD - 2) mbar_arrive(bar_pre);
                if (h == NHEAD - 1) mbar_arrive(bar_done);
            }
        }
        if (lane == 0) TS(5);
        return;
    }

    if (warp < NCW) {
        uint32_t koff[4], voff[4];
#pragma unroll
        for (int j = 0; j < 4; j++) {
            koff[j] = (mi & 1) * 1024 + rr * 128 + ((((j << 1) | (mi >> 1)) ^ rr) << 4);
            voff[j] = STAGE_BYTES / 2 + (mi >> 1) * 1024 + rr * 128 + ((((j << 1) | (mi & 1)) ^ rr) << 4);
        }
        float o[8][4];
        float m_run = -INFINITY, l_run = 0.f;
#pragma unroll
        for (int i = 0; i < 8; i++) { o[i][0] = o[i][1] = o[i][2] = o[i][3] = 0.f; }
        uint32_t qf[8][2];
#pragma unroll
        for (int kk = 0; kk < 8; kk++) { qf[kk][0] = 0x3f803f80u; qf[kk][1] = 0x3f803f80u; }
        int cur = -1;
        int s = warp % NST;
        uint32_t ph = 0;
        __syncthreads();
        bool live = (P.three != 3);
        while (true) {
            if (live) {
                mbar_wait(bar_full + 8 * s, ph);
                const int tile = tile_info[s];
                const int head = tile < 0 ? NHEAD : (tile >> TPH_SHIFT);
                if (head != cur) {
                    while (cur < head) {
                        if (cur >= 0) {
                            const int slot = cur & 1;
                            mbar_wait(bar_fle + 8 * slot, ((cur >> 1) & 1) ^ 1);
                            float* dst = fl + (slot * 4 + warp) * 132;
                            float lt = l_run;
                            lt += __shfl_xor_sync(0xffffffffu, lt, 4);
                            lt += __shfl_xor_sync(0xffffffffu, lt, 8);
                            lt += __shfl_xor_sync(0xffffffffu, lt, 16);
                            if (lane == 0) { dst[128] = m_run; dst[129] = lt; }
#pragma unroll
                            for (int i = 0; i < 8; i++)
                                if (t4 == (i & 3)) { dst[i * 16 + g] = o[i][0]; dst[i * 16 + g + 8] = o[i][2]; }
                            __syncwarp();
                            if (lane == 0) mbar_arrive(bar_flf + 8 * slot);
                        }
#pragma unroll
                        for (int i = 0; i < 8; i++) { o[i][0] = o[i][1] = o[i][2] = o[i][3] = 0.f; }
                        m_run = -INFINITY; l_run = 0.f;
                        cur++;
                    }
                    if (tile < 0) break;
                    if (cur > 0) mbar_wait(bar_q2, 0);
#pragma unroll
                    for (int kk = 0; kk < 8; kk++) { qf[kk][0] = q_s[cur * 64 + kk * 8 + t4]; qf[kk][1] = q_s[cur * 64 + kk * 8 + 4 + t4]; }
                }
            }
            const uint32_t st = sb + SM_KV + s * STAGE_BYTES;
            float sa[2][2][4];
#pragma unroll
            for (int a = 0; a < 2; a++)
#pragma unroll
                for (int b = 0; b < 2; b++) { sa[a][b][0] = sa[a][b][1] = sa[a][b][2] = sa[a][b][3] = 0.f; }
#pragma unroll
            for (int kk = 0; kk < 8; kk++) {
#pragma unroll
                for (int kg = 0; kg < 2; kg++) {
                    uint32_t a[4];
                    ldsm4(a, st + koff[kk & 3] + (kk >> 2) * 4096 + kg * 2048);
                    mma16816(sa[kg][kk & 1], a, qf[kk][0], qf[kk][1]);
                }
            }
            uint32_t va[8][4];
#pragma unroll
            for (int mt = 0; mt < 8; mt++) ldsm4t(va[mt], st + voff[mt & 3] + (mt >> 2) * 4096);
            const float scale = 0.08838834764831845f;
            const uint32_t r01 = pack_bf16(sa[0][0][0] + sa[0][1][0], sa[0][0][2] + sa[0][1][2]);
            const uint32_t r23 = pack_bf16(sa[1][0][0] + sa[1][1][0], sa[1][0][2] + sa[1][1][2]);
            const uint32_t s01 = pack_bf16(bf_lo(r01) * scale, bf_hi(r01) * scale);
            const uint32_t s23 = pack_bf16(bf_lo(r23) * scale, bf_hi(r23) * scale);
            const float s0 = bf_lo(s01), s1 = bf_hi(s01), s2 = bf_lo(s23), s3 = bf_hi(s23);
            float mx = fmaxf(fmaxf(s0, s1), fmaxf(s2, s3));
            mx = fmaxf(mx, __shfl_xor_sync(0xffffffffu, mx, 4));
            mx = fmaxf(mx, __shfl_xor_sync(0xffffffffu, mx, 8));
            mx = fmaxf(mx, __shfl_xor_sync(0xffffffffu, mx, 16));
            if (mx > m_run || !live) {
                const float corr = ex2((m_run - mx) * LOG2E);
                l_run *= corr;
#pragma unroll
                for (int i = 0; i < 8; i++) { o[i][0] *= corr; o[i][1] *= corr; o[i][2] *= corr; o[i][3] *= corr; }
                m_run = mx;
            }
            const float ml = m_run * LOG2E;
            const float p0 = ex2(fmaf(s0, LOG2E, -ml)), p1 = ex2(fmaf(s1, LOG2E, -ml));
            const float p2 = ex2(fmaf(s2, LOG2E, -ml)), p3 = ex2(fmaf(s3, LOG2E, -ml));
            l_run += (p0 + p1) + (p2 + p3);
            const uint32_t b0 = movm(pack_bf16(p0, p0)), b1 = movm(pack_bf16(p1, p1));
            const uint32_t b2 = movm(pack_bf16(p2, p2)), b3 = movm(pack_bf16(p3, p3));
#pragma unroll
            for (int mt = 0; mt < 8; mt++) mma16816(o[mt], va[mt], b0, b1);
#pragma unroll
            for (int mt = 0; mt < 8; mt++) ldsm4t(va[mt], st + voff[mt & 3] + (mt >> 2) * 4096 + 2048);
            __syncwarp();
            if (lane == 0 && live) mbar_arrive(bar_empty + 8 * s);
#pragma unroll
            for (int mt = 0; mt < 8; mt++) mma16816(o[mt], va[mt], b2, b3);
            if (live) {
                s += NCW;
                if (s >= NST) { s -= NST; ph ^= 1; }
            } else {
                mbar_wait(bar_q, 0);
                live = true;
            }
        }
        if (tid == 0) TS(4);
        return;
    }

    const int ht = tid - 128, hw = warp - 4;
    uint32_t* vec = reinterpret_cast<uint32_t*>(smem + SM_VEC);
    float* red = reinterpret_cast<float*>(smem + SM_RED);
    float2* stat = reinterpret_cast<float2*>(smem + SM_STAT);

    const uint2 cw = reinterpret_cast<const uint2*>(P.c)[ht];
    const uint2 xw = reinterpret_cast<const uint2*>(P.x)[ht];
    const int n0 = hw * 128 + t4 * 16 + g;
    const unsigned short* xs = reinterpret_cast<const unsigned short*>(P.x) + n0;
    const unsigned short xg0 = xs[0], xg1 = xs[8], xg2 = xs[64], xg3 = xs[72];
    const uint32_t epoch = *reinterpret_cast<volatile unsigned*>(&g_epoch);
    const int qc = (cta + MOD0_CTAS) & (Q_CTAS - 1);
    if (hw == 0 && lane < 16) {
        if (cta < MOD_CTAS) ll_store(&g_mod[cta * 16 + lane], 0u, 0u);
        if (cta < Q_CTAS) ll_store(&g_q[qc * 16 + lane], 0u, 0u);
    }
    if (cta < MOD0_CTAS) load_slice(sb + SM_WGU, P.w_mod + cta * 32, 3072, ht);
    if (cta < Q_CTAS && !(WQ_LATE && cta < MOD0_CTAS)) load_slice(sb + SM_WO, P.wq + qc * 32, 4096, ht);
    uint32_t flag;
    uint2 xp;
    asm volatile("add.u32 %0, %1, 1;" : "=r"(flag) : "r"(epoch));
    asm volatile("mov.b32 %0, {%1, %2};" : "=r"(xp.x) : "h"(xg0), "h"(xg1));
    asm volatile("mov.b32 %0, {%1, %2};" : "=r"(xp.y) : "h"(xg2), "h"(xg3));
    const uint32_t sc0 = pack_bf16(silu_bf(bf_lo(cw.x)), silu_bf(bf_hi(cw.x)));
    const uint32_t sc1 = pack_bf16(silu_bf(bf_lo(cw.y)), silu_bf(bf_hi(cw.y)));
    *reinterpret_cast<uint2*>(vec + 2 * ht) = make_uint2(sc0, sc1);
    __syncthreads();
    if (ht == 0) TS(9);
    const float4 xv = make_float4(bf_lo(xw.x), bf_hi(xw.x), bf_lo(xw.y), bf_hi(xw.y));
    const float4 ln = layernorm512(xv, stat);
    if (cta < MOD0_CTAS) {
        asm volatile("cp.async.wait_group %0;" ::"n"(WQ_LATE ? 0 : 1) : "memory");
        __syncwarp();
        if (lane == 0) mbar_arrive(bar_go);
        hbar();
        const float r = gemv512x32(sb + SM_WGU, vec, red);
        const float o2 = __shfl_xor_sync(0xffffffffu, r, 1);
        if (hw == 0 && (lane & 1) == 0) ll_store(&g_mod[cta * 16 + (lane >> 1)], pack_bf16(r, o2), flag);
        if (WQ_LATE) load_slice(sb + SM_WO, P.wq + qc * 32, 4096, ht);
    }
    if (PRO_WAITQ) asm volatile("cp.async.wait_group 0;" ::: "memory");
    if (ht == 0) TS(11);
    {
        u64 v[4] = {0, 0, 0, 0};
        unsigned spins = 0;
        while (true) {
            ll_load2(&g_mod[2 * ht], v[0], v[1]);
            ll_load2(&g_mod[256 + 2 * ht], v[2], v[3]);
            if (ll_ok(v[0], flag) && ll_ok(v[1], flag) && ll_ok(v[2], flag) && ll_ok(v[3], flag)) break;
            if (++spins > SPIN_LIMIT) __trap();
        }
        const uint32_t s0 = (uint32_t)v[0], s1 = (uint32_t)v[1], c0 = (uint32_t)v[2], c1 = (uint32_t)v[3];
        const uint32_t h0 = pack_bf16(rbf(ln.x * rbf(1.f + bf_lo(c0))) + bf_lo(s0), rbf(ln.y * rbf(1.f + bf_hi(c0))) + bf_hi(s0));
        const uint32_t h1 = pack_bf16(rbf(ln.z * rbf(1.f + bf_lo(c1))) + bf_lo(s1), rbf(ln.w * rbf(1.f + bf_hi(c1))) + bf_hi(s1));
        asm volatile("cp.async.wait_group 0;" ::: "memory");
        hbar();
        *reinterpret_cast<uint2*>(vec + 2 * ht) = make_uint2(h0, h1);
    }
    hbar();
    if (ht == 0) TS(1);
    if (cta < Q_CTAS) {
        const float r = gemv512x32(sb + SM_WO, vec, red);
        const float o2 = __shfl_xor_sync(0xffffffffu, r, 1);
        if (hw == 0 && (lane & 1) == 0) ll_store(&g_q[qc * 16 + (lane >> 1)], pack_bf16(r, o2), flag);
    }
    if (ht == 0) TS(12);
    if (hw == 0) {
        u64 a = 0, b = 0;
        unsigned spins = 0;
        while (true) {
            ll_load2(&g_q[2 * lane], a, b);
            if (__all_sync(0xffffffffu, ll_ok(a, flag) && ll_ok(b, flag))) break;
            if (++spins > SPIN_LIMIT) __trap();
        }
        *reinterpret_cast<uint2*>(&q_s[2 * lane]) = make_uint2((uint32_t)a, (uint32_t)b);
        __syncwarp();
        if (lane == 0) { mbar_arrive(bar_q); TS(2); }
    }
    {
        u64 v[16];
#pragma unroll
        for (int k = 0; k < 16; k++) v[k] = 0;
        unsigned spins = 0;
        while (true) {
            bool ok = true;
#pragma unroll
            for (int k = 0; k < 8; k++) ll_load2(&g_q[k * 256 + ht * 2], v[2 * k], v[2 * k + 1]);
#pragma unroll
            for (int k = 0; k < 16; k++) ok = ok && ll_ok(v[k], flag);
            if (ok) break;
            if (++spins > SPIN_LIMIT) __trap();
        }
#pragma unroll
        for (int k = 0; k < 8; k++)
            *reinterpret_cast<uint2*>(&q_s[k * 256 + ht * 2]) = make_uint2((uint32_t)v[2 * k], (uint32_t)v[2 * k + 1]);
    }
    hbar();
    if (ht == 0) mbar_arrive(bar_q2);
    if (cta >= Q_CTAS) return;

    if (cta >= MOD0_CTAS && cta < MOD_CTAS) {
        load_slice(sb + SM_WGU, P.w_mod + cta * 32, 3072, ht);
        *reinterpret_cast<uint2*>(vec + 2 * ht) = make_uint2(sc0, sc1);
        asm volatile("cp.async.wait_group 0;" ::: "memory");
        hbar();
        const float r = gemv512x32(sb + SM_WGU, vec, red);
        const float o2 = __shfl_xor_sync(0xffffffffu, r, 1);
        if (hw == 0 && (lane & 1) == 0) ll_store(&g_mod[cta * 16 + (lane >> 1)], pack_bf16(r, o2), flag);
    }
    hbar();
    asm volatile("fence.proxy.async.shared::cta;" ::: "memory");
    if (hw == 0 && !EARLY_BG) {
        if (lane == 0) mbar_expect_tx(bar_w, 32 * 1024);
        __syncwarp();
        bulk_g2s(sb + SM_WO + lane * WROW, P.wo + (size_t)(cta * 32 + lane) * D_MODEL, 1024, bar_w);
    }
    uint32_t md[8] = {0, 0, 0, 0, 0, 0, 0, 0};
    asm volatile("cp.async.wait_all;" ::: "memory");
    mbar_wait(bar_w, 0);
    hbar();

    const uint32_t tag = flag & 3u;
    volatile uint32_t* tgo_s = reinterpret_cast<volatile uint32_t*>(smem + SM_FIN);
    uint32_t t_go = 0;
    const int h = cta >> 2, j = cta & 3;
    const bool last_unit = (h == NHEAD - 1);
#pragma unroll 1
    for (int pass = 0; pass < P.three; pass++) {
        const uint32_t c_live = last_unit ? (pass == 2) : (pass == 1);
        if (pass == 1 && last_unit) mbar_wait_long(bar_pre, 0);
        if (pass < 2 || last_unit) {
            const uint32_t live = c_live;
            uint4 rp = make_uint4(0, 0, 0, 0);
            if (live && !last_unit) { mbar_wait_long(bar_own, 0); __nanosleep(COMBINE_DELAY_NS); }
            {
                const uint32_t* Rp = &g_R[(size_t)((h - 1) * 4 + j) * D_MODEL + 4 * ht];
                const uint32_t lv = live && h > 0;
                unsigned spins = 0;
                while (true) {
                    tg_load4(Rp, rp, lv);
                    if (__all_sync(0xffffffffu, !lv || tg_bad4(rp, tag) == 0)) break;
                    if (++spins > SPIN_LIMIT) __trap();
                    __nanosleep(500);
                }
            }
            const int sub = lane >> 3, c8 = lane & 7;
            const uint32_t* po = &g_po[((size_t)((h % PO_RING) * 4 + j) * GRID + 4 * sub + hw) * 32 + 4 * c8];
            const uint32_t* ph = &g_ph[(h * GRID + lane) * 2];
            uint32_t hm[5], hl[5];
            uint4 ov[9];
#pragma unroll
            for (int k = 0; k < 5; k++) { hm[k] = 0xff800000u | tag; hl[k] = tag; }
            const uint32_t ptag = PO_RING == 32 ? tag : (((h / PO_RING) + 1) & 3);
#pragma unroll
            for (int i = 0; i < 9; i++) ov[i] = make_uint4(ptag, ptag, ptag, ptag);
            uint32_t wa[16][4];
#pragma unroll
            for (int i = 0; i < 8; i++) {
                const uint32_t base = sb + SM_WO + ((mi >> 1) * 8 + rr) * WROW + ((hw * 8 + i) * 16 + (mi & 1) * 8) * 2;
                ldsm4t(wa[2 * i], base);
                ldsm4t(wa[2 * i + 1], base + 16 * WROW);
            }
            if (live && last_unit) mbar_wait_long(bar_own, 0);
            unsigned spins = 0;
            uint32_t need = live ? ((lane < GRID - 128 ? 0x1fu : 0xfu) | (sub == 0 ? 0x3fe0u : 0x1fe0u)) : 0u;
            while (true) {
#pragma unroll
                for (int k = 0; k < 5; k++) tg_load2(ph + 64 * k, hm[k], hl[k], need & (1u << k));
#pragma unroll
                for (int i = 0; i < 9; i++) tg_load4(po + i * 16 * 32, ov[i], need & (32u << i));
                need = 0;
#pragma unroll
                for (int k = 0; k < 5; k++) need |= (((hm[k] ^ tag) | (hl[k] ^ tag)) & 3u) ? (1u << k) : 0u;
#pragma unroll
                for (int i = 0; i < 9; i++) need |= tg_bad4(ov[i], ptag) ? (32u << i) : 0u;
                if (!live) need = 0;
                if (!__any_sync(0xffffffffu, need != 0)) break;
                if (++spins > SPIN_LIMIT) __trap();
                if (!last_unit) __nanosleep(1000);
            }
            TSW(14);
            CKS(0);
            if (last_unit) {
                const uint32_t wv = (gtime32() & ~3u) | (live ? tag : (tag ^ 1u));
                asm volatile("{\n.reg .pred p;\nsetp.ne.u32 p, %2, 0;\n@p st.relaxed.gpu.global.u32 [%0], %1;\n}"
                             ::"l"(&g_W[((j * 4 + hw) * WREP + (lane & (WREP - 1))) * 32]), "r"(wv), "r"((uint32_t)(pass > 0 && lane < WREP)) : "memory");
            }
            int mk = (int)0x807fffff;
#pragma unroll
            for (int k = 0; k < 5; k++) {
                const int b = (int)(hm[k] & ~3u);
                mk = max(mk, b ^ ((b >> 31) & 0x7fffffff));
            }
            mk = __reduce_max_sync(0xffffffffu, mk);
            const float M = __int_as_float(mk ^ ((mk >> 31) & 0x7fffffff));
            float wt[5], L = 0.f;
#pragma unroll
            for (int k = 0; k < 5; k++) {
                wt[k] = ex2((tg_dec(hm[k]) - M) * LOG2E);
                L = fmaf(wt[k], tg_dec(hl[k]), L);
            }
            float wv[9];
#pragma unroll
            for (int i = 0; i < 9; i++) wv[i] = __shfl_sync(0xffffffffu, wt[i >> 1], (16 * (i & 1) + 4 * sub + hw) & 31);
            L += __shfl_xor_sync(0xffffffffu, L, 1);
            float a0 = 0.f, a1 = 0.f, a2 = 0.f, a3 = 0.f;
#pragma unroll
            for (int i = 0; i < 9; i++) {
                a0 = fmaf(wv[i], tg_val(ov[i].x), a0); a1 = fmaf(wv[i], tg_val(ov[i].y), a1);
                a2 = fmaf(wv[i], tg_val(ov[i].z), a2); a3 = fmaf(wv[i], tg_val(ov[i].w), a3);
                if (i == 2) L += __shfl_xor_sync(0xffffffffu, L, 2);
                if (i == 6) L += __shfl_xor_sync(0xffffffffu, L, 4);
            }
            a0 += __shfl_xor_sync(0xffffffffu, a0, 8); a1 += __shfl_xor_sync(0xffffffffu, a1, 8);
            a2 += __shfl_xor_sync(0xffffffffu, a2, 8); a3 += __shfl_xor_sync(0xffffffffu, a3, 8);
            L += __shfl_xor_sync(0xffffffffu, L, 8);
            a0 += __shfl_xor_sync(0xffffffffu, a0, 16); a1 += __shfl_xor_sync(0xffffffffu, a1, 16);
            a2 += __shfl_xor_sync(0xffffffffu, a2, 16); a3 += __shfl_xor_sync(0xffffffffu, a3, 16);
            L += __shfl_xor_sync(0xffffffffu, L, 16);
            if (lane < 8) *reinterpret_cast<float4*>(red + hw * 32 + 4 * lane) = make_float4(a0, a1, a2, a3);
            CKS(1);
            hbar();
            const float of = __fdividef((red[lane] + red[32 + lane]) + (red[64 + lane] + red[96 + lane]), L);
            const uint32_t pr = pack_bf16(of, __shfl_xor_sync(0xffffffffu, of, 1));
            const uint32_t ob0 = __shfl_sync(0xffffffffu, pr, 2 * t4), ob1 = __shfl_sync(0xffffffffu, pr, 2 * t4 + 8);
            const uint32_t ob2 = __shfl_sync(0xffffffffu, pr, 2 * t4 + 16), ob3 = __shfl_sync(0xffffffffu, pr, 2 * t4 + 24);
            float y[8][4];
#pragma unroll
            for (int i = 0; i < 8; i++) {
                y[i][0] = y[i][1] = y[i][2] = y[i][3] = 0.f;
                mma16816(y[i], wa[2 * i], ob0, ob1);
            }
#pragma unroll
            for (int i = 0; i < 8; i++) mma16816(y[i], wa[2 * i + 1], ob2, ob3);
            const float ya = t4 == 0 ? y[0][0] : t4 == 1 ? y[1][0] : t4 == 2 ? y[2][0] : y[3][0];
            const float yb = t4 == 0 ? y[0][2] : t4 == 1 ? y[1][2] : t4 == 2 ? y[2][2] : y[3][2];
            const float yc = t4 == 0 ? y[4][0] : t4 == 1 ? y[5][0] : t4 == 2 ? y[6][0] : y[7][0];
            const float yd = t4 == 0 ? y[4][2] : t4 == 1 ? y[5][2] : t4 == 2 ? y[6][2] : y[7][2];
            CKS(2);
            uint32_t* Rn = &g_R[(size_t)(h * 4 + j) * D_MODEL + 4 * ht];
            const uint32_t stag = live ? tag : (tag ^ 1u), sl = pass > 0;
#pragma unroll
            for (int r = 0; r < RREP; r++)
                tg_store4(Rn + r * 4 * D_MODEL, tg_val(rp.x) + ya, tg_val(rp.y) + yb, tg_val(rp.z) + yc, tg_val(rp.w) + yd, stag, sl && (r == 0 || last_unit));
            TSW(15);
        }
        if (pass == 1) {
            mbar_wait_long(bar_pre, 0);
            u64 v[16];
#pragma unroll
            for (int k = 0; k < 16; k++) v[k] = 0;
            unsigned spins = 0;
            while (true) {
                bool ok = true;
#pragma unroll
                for (int k = 0; k < 16; k++)
                    ll_load(&g_mod[(2 + (k >> 2)) * 256 + (n0 >> 1) + ((k & 1) ? 4 : 0) + ((k & 2) ? 32 : 0)], v[k]);
#pragma unroll
                for (int k = 0; k < 16; k++) ok = ok && ll_ok(v[k], flag);
                if (ok) break;
                if (++spins > SPIN_LIMIT) __trap();
                __nanosleep(500);
            }
            const uint32_t sel = (g & 1) ? 0x7632u : 0x5410u;
#pragma unroll
            for (int k = 0; k < 8; k++) md[k] = __byte_perm((uint32_t)v[2 * k], (uint32_t)v[2 * k + 1], sel);
        }
        const uint32_t live = (pass == 2);
        if (cta < FFN_CTAS) {
            if (live) mbar_wait_long(WL_K >= 0 ? bar_wl : bar_done, 0);
            const int row0 = ht >> 2, ch = ht & 3;
            uint32_t d = sb + SM_WGU + row0 * 64 + ((ch ^ ((row0 >> 1) & 3)) << 4);
            const __nv_bfloat16* s = (ch < 2 ? P.w_gate : P.w_up) + (size_t)row0 * FF + cta * 16 + (ch & 1) * 8;
#pragma unroll 1
            for (int r = 0; r < WL_ROUNDS; r++) {
#pragma unroll
                for (int i = 0; i < 16 / WL_ROUNDS; i++) {
                    cp_async16_p(d, s, live);
                    d += 32 * 64;
                    s += (size_t)32 * FF;
                }
                cp_async_commit();
                asm volatile("cp.async.wait_group %0;" ::"n"(WL_WIN) : "memory");
            }
            if (hw == 0) {
                mbar_expect_tx_p(bar_w2, 16 * 1024, live && lane == 0);
                __syncwarp();
                bulk_g2s_p(sb + SM_WD + lane * WROW, P.w_down + (size_t)(cta * 16 + (lane & 15)) * D_MODEL, 1024, bar_w2, live && lane < 16);
            }
            asm volatile("cp.async.wait_all;" ::: "memory");
            hbar();
            if (ht == 0 && live) TS(10);
        }
        uint32_t ga[8][4], ua[8][4];
        {
            const int row0 = hw * 128 + (mi >> 1) * 8 + rr;
            const int sw = (row0 >> 1) & 3;
            const uint32_t a0 = sb + SM_WGU + row0 * 64 + (((mi & 1) ^ sw) << 4);
            const uint32_t a1 = sb + SM_WGU + row0 * 64 + (((2 + (mi & 1)) ^ sw) << 4);
#pragma unroll
            for (int ks = 0; ks < 8; ks++) { ldsm4t(ga[ks], a0 + ks * 1024); ldsm4t(ua[ks], a1 + ks * 1024); }
        }
        uint32_t da[8][4];
        if (live && cta < FFN_CTAS) mbar_wait(bar_w2, 0);
#pragma unroll
        for (int i = 0; i < 8; i++)
            ldsm4t(da[i], sb + SM_WD + ((mi >> 1) * 8 + rr) * WROW + ((hw * 8 + i) * 16 + (mi & 1) * 8) * 2);
        float4 x1;
        {
            uint4 v[4];
#pragma unroll
            for (int k = 0; k < 4; k++) v[k] = make_uint4(0, 0, 0, 0);
            const uint32_t* R = &g_R[(size_t)((NHEAD - 1 + (cta % RREP)) * 4) * D_MODEL + 4 * ht];
            if (live) mbar_wait_long(bar_done, 0);
            unsigned spins = 0;
            if (hw == 0) {
                uint32_t w = tag;
                const uint32_t* Wp = &g_W[((lane & 15) * WREP + (cta & (WREP - 1))) * 32];
                const uint32_t lv = live && lane < 16;
                while (true) {
                    tg_load(Wp, w, lv);
                    if (__all_sync(0xffffffffu, ((w ^ tag) & 3u) == 0)) break;
                    if (++spins > SPIN_LIMIT) __trap();
                }
                const uint32_t now = gtime32();
                int dl = lv ? (int)((w & ~3u) - now) : -1000000;
                dl = __reduce_max_sync(0xffffffffu, dl);
                dl = min(dl, 0);
                if (lane == 0) *tgo_s = now + (uint32_t)dl + R_DELAY_NS;
            }
            hbar();
            t_go = *tgo_s;
            if (live) spin_until(t_go);
            spins = 0;
            uint32_t need = (live && (cta < FFN_CTAS || ht == cta)) ? 0xfu : 0u;
            const uint32_t lr = need;
            while (true) {
#pragma unroll
                for (int k = 0; k < 4; k++) tg_load4(R + k * D_MODEL, v[k], need & (1u << k));
                need = 0;
#pragma unroll
                for (int k = 0; k < 4; k++) need |= tg_bad4(v[k], tag) ? (1u << k) : 0u;
                need &= lr;
                if (!__any_sync(0xffffffffu, need != 0)) break;
                if (++spins > SPIN_LIMIT) __trap();
            }
            const float a0 = (tg_val(v[0].x) + tg_val(v[1].x)) + (tg_val(v[2].x) + tg_val(v[3].x));
            const float a1 = (tg_val(v[0].y) + tg_val(v[1].y)) + (tg_val(v[2].y) + tg_val(v[3].y));
            const float a2 = (tg_val(v[0].z) + tg_val(v[1].z)) + (tg_val(v[2].z) + tg_val(v[3].z));
            const float a3 = (tg_val(v[0].w) + tg_val(v[1].w)) + (tg_val(v[2].w) + tg_val(v[3].w));
            x1.x = rbf(bf_lo(xp.x) + rbf(bf_lo(md[0]) * rbf(a0)));
            x1.y = rbf(bf_hi(xp.x) + rbf(bf_hi(md[0]) * rbf(a1)));
            x1.z = rbf(bf_lo(xp.y) + rbf(bf_lo(md[1]) * rbf(a2)));
            x1.w = rbf(bf_hi(xp.y) + rbf(bf_hi(md[1]) * rbf(a3)));
        }
        TSW(6);
        CKS(3);
        if (cta < FFN_CTAS) {
            const float4 y = layernorm512(x1, stat);
            CKS(4);
            const uint32_t h0 = pack_bf16(rbf(y.x * rbf(1.f + bf_lo(md[4]))) + bf_lo(md[2]), rbf(y.y * rbf(1.f + bf_hi(md[4]))) + bf_hi(md[2]));
            const uint32_t h1 = pack_bf16(rbf(y.z * rbf(1.f + bf_lo(md[5]))) + bf_lo(md[3]), rbf(y.w * rbf(1.f + bf_hi(md[5]))) + bf_hi(md[3]));
            {
                unsigned short* v16 = reinterpret_cast<unsigned short*>(vec) + n0;
                v16[0] = (unsigned short)h0; v16[8] = (unsigned short)(h0 >> 16);
                v16[64] = (unsigned short)h1; v16[72] = (unsigned short)(h1 >> 16);
            }
            __syncwarp();
            CKS(5);
            float c0[4][4], c1[4][4];
#pragma unroll
            for (int i = 0; i < 4; i++) { c0[i][0] = c0[i][1] = c0[i][2] = c0[i][3] = 0.f; c1[i][0] = c1[i][1] = c1[i][2] = c1[i][3] = 0.f; }
            const uint32_t* vp = vec + hw * 64 + t4;
            uint32_t bf[8][2];
#pragma unroll
            for (int ks = 0; ks < 8; ks++) { bf[ks][0] = vp[ks * 8]; bf[ks][1] = vp[ks * 8 + 4]; }
#pragma unroll
            for (int ks = 0; ks < 8; ks++) {
                mma16816(c0[ks & 3], ga[ks], bf[ks][0], bf[ks][1]);
                mma16816(c1[ks & 3], ua[ks], bf[ks][0], bf[ks][1]);
            }
            if (t4 == 0) {
                red[hw * 32 + g] = (c0[0][0] + c0[1][0]) + (c0[2][0] + c0[3][0]);
                red[hw * 32 + 8 + g] = (c0[0][2] + c0[1][2]) + (c0[2][2] + c0[3][2]);
                red[hw * 32 + 16 + g] = (c1[0][0] + c1[1][0]) + (c1[2][0] + c1[3][0]);
                red[hw * 32 + 24 + g] = (c1[0][2] + c1[1][2]) + (c1[2][2] + c1[3][2]);
            }
            hbar();
            const float gx = rbf((red[lane] + red[32 + lane]) + (red[64 + lane] + red[96 + lane]));
            CKS(6);
            const float uu = __shfl_down_sync(0xffffffffu, gx, 16);
            const float inner = 0.7978845608028654f * (gx + 0.044715f * gx * gx * gx);
            const float ge = rbf(__fdividef(gx, 1.f + ex2(-2.f * LOG2E * inner)));
            const float act = rbf(ge * uu);
            const uint32_t ap = pack_bf16(act, __shfl_xor_sync(0xffffffffu, act, 1));
            const uint32_t ab0 = __shfl_sync(0xffffffffu, ap, 2 * t4), ab1 = __shfl_sync(0xffffffffu, ap, 2 * t4 + 8);
            CKS(7);
            float f[8][4];
#pragma unroll
            for (int i = 0; i < 8; i++) {
                f[i][0] = f[i][1] = f[i][2] = f[i][3] = 0.f;
                mma16816(f[i], da[i], ab0, ab1);
            }
            const float fa = t4 == 0 ? f[0][0] : t4 == 1 ? f[1][0] : t4 == 2 ? f[2][0] : f[3][0];
            const float fb = t4 == 0 ? f[0][2] : t4 == 1 ? f[1][2] : t4 == 2 ? f[2][2] : f[3][2];
            const float fc = t4 == 0 ? f[4][0] : t4 == 1 ? f[5][0] : t4 == 2 ? f[6][0] : f[7][0];
            const float fd = t4 == 0 ? f[4][2] : t4 == 1 ? f[5][2] : t4 == 2 ? f[6][2] : f[7][2];
            CKS(8);
            tg_store4(&g_f[((ht >> 1) * FFN_CTAS + cta) * 8 + (ht & 1) * 4], fa, fb, fc, fd, live ? tag : (tag ^ 1u), pass > 0);
        }
        TSW(7);
        CKS(9);
        if (hw == (cta >> 5)) {
            uint4 v[4];
#pragma unroll
            for (int k = 0; k < 4; k++) v[k] = make_uint4(tag, tag, tag, tag);
            const uint32_t* src = &g_f[((cta >> 1) * FFN_CTAS + lane) * 8 + (cta & 1) * 4];
            unsigned spins = 0;
            uint32_t need = live ? (lane < FFN_CTAS - 96 ? 0xfu : 0x7u) : 0u;
            if (live) spin_until(cta < FFN_CTAS ? gtime32() + F_DELAY_NS : t_go + F_DELAY2_NS);
            while (true) {
#pragma unroll
                for (int k = 0; k < 4; k++) tg_load4(src + k * 32 * 8, v[k], need & (1u << k));
                need = 0;
#pragma unroll
                for (int k = 0; k < 4; k++) need |= tg_bad4(v[k], tag) ? (1u << k) : 0u;
                if (!live) need = 0;
                if (!__any_sync(0xffffffffu, need != 0)) break;
                if (++spins > SPIN_LIMIT) __trap();
            }
            float s0 = (tg_val(v[0].x) + tg_val(v[1].x)) + (tg_val(v[2].x) + tg_val(v[3].x));
            float s1 = (tg_val(v[0].y) + tg_val(v[1].y)) + (tg_val(v[2].y) + tg_val(v[3].y));
            float s2 = (tg_val(v[0].z) + tg_val(v[1].z)) + (tg_val(v[2].z) + tg_val(v[3].z));
            float s3 = (tg_val(v[0].w) + tg_val(v[1].w)) + (tg_val(v[2].w) + tg_val(v[3].w));
#pragma unroll
            for (int o2 = 1; o2 < 32; o2 <<= 1) {
                s0 += __shfl_xor_sync(0xffffffffu, s0, o2);
                s1 += __shfl_xor_sync(0xffffffffu, s1, o2);
                s2 += __shfl_xor_sync(0xffffffffu, s2, o2);
                s3 += __shfl_xor_sync(0xffffffffu, s3, o2);
            }
            if (ht == cta) {
                const uint32_t o0 = pack_bf16(x1.x + rbf(bf_lo(md[6]) * rbf(s0)), x1.y + rbf(bf_hi(md[6]) * rbf(s1)));
                const uint32_t o1 = pack_bf16(x1.z + rbf(bf_lo(md[7]) * rbf(s2)), x1.w + rbf(bf_hi(md[7]) * rbf(s3)));
                unsigned short* o16 = reinterpret_cast<unsigned short*>(P.out) + n0;
                asm volatile("{\n.reg .pred p;\nsetp.ne.u32 p, %5, 0;\n"
                             "@p st.global.b16 [%0], %1;\n@p st.global.b16 [%0+16], %2;\n@p st.global.b16 [%0+128], %3;\n@p st.global.b16 [%0+144], %4;\n}"
                             ::"l"(o16), "h"((unsigned short)o0), "h"((unsigned short)(o0 >> 16)), "h"((unsigned short)o1), "h"((unsigned short)(o1 >> 16)), "r"(live) : "memory");
                asm volatile("{\n.reg .pred p;\nsetp.ne.u32 p, %3, 0;\n@p st.global.u32 [%0], 0;\n@p st.global.u32 [%1], %2;\n}"
                             ::"l"(&g_ctr), "l"(&g_epoch), "r"(flag), "r"((uint32_t)(live && cta == 0)) : "memory");
            }
        }
        if (pass < 2) hbar();
    }
}

typedef CUresult (*EncodeTiledFn)(CUtensorMap*, CUtensorMapDataType, cuuint32_t, void*, const cuuint64_t*, const cuuint64_t*,
                                  const cuuint32_t*, const cuuint32_t*, CUtensorMapInterleave, CUtensorMapSwizzle,
                                  CUtensorMapL2promotion, CUtensorMapFloatOOBfill);

bool make_kv_map(EncodeTiledFn enc, CUtensorMap* m, void* base) {
    cuuint64_t gd[3] = {64, (cuuint64_t)NHEAD * SEQ, 2};
    cuuint64_t gs[2] = {256, 128};
    cuuint32_t bd[3] = {64, TILE, 2};
    cuuint32_t es[3] = {1, 1, 1};
    return enc(m, CU_TENSOR_MAP_DATA_TYPE_BFLOAT16, 3, base, gd, gs, bd, es, CU_TENSOR_MAP_INTERLEAVE_NONE,
               CU_TENSOR_MAP_SWIZZLE_128B, CU_TENSOR_MAP_L2_PROMOTION_L2_256B, CU_TENSOR_MAP_FLOAT_OOB_FILL_NONE) == CUDA_SUCCESS;
}

}

extern "C" void kernel_launch(void* const* d_in, const int* in_sizes, int n_in, void* d_out, int out_size) {
    (void)in_sizes; (void)n_in; (void)out_size;
    static EncodeTiledFn enc = nullptr;
    static CUtensorMap map_k, map_v;
    static void *k_ptr = nullptr, *v_ptr = nullptr;
    if (!enc) {
        void* fn = nullptr;
        cudaDriverEntryPointQueryResult qr;
        if (cudaGetDriverEntryPoint("cuTensorMapEncodeTiled", &fn, cudaEnableDefault, &qr) != cudaSuccess || !fn) {
            fprintf(stderr, "cuTensorMapEncodeTiled not available\n");
            return;
        }
        enc = (EncodeTiledFn)fn;
        cudaFuncSetAttribute(fused_decode_kernel, cudaFuncAttributeMaxDynamicSharedMemorySize, SM_TOTAL);
    }
    if (k_ptr != d_in[1] || v_ptr != d_in[2]) {
        if (!make_kv_map(enc, &map_k, d_in[1]) || !make_kv_map(enc, &map_v, d_in[2])) {
            fprintf(stderr, "tensor map encode failed\n");
            return;
        }
        k_ptr = d_in[1];
        v_ptr = d_in[2];
    }
    Params P;
    P.x = (const __nv_bfloat16*)d_in[0];
    P.wq = (const __nv_bfloat16*)d_in[3];
    P.wo = (const __nv_bfloat16*)d_in[4];
    P.w_gate = (const __nv_bfloat16*)d_in[6];
    P.w_up = (const __nv_bfloat16*)d_in[7];
    P.w_down = (const __nv_bfloat16*)d_in[8];
    P.c = (const __nv_bfloat16*)d_in[9];
    P.w_mod = (const __nv_bfloat16*)d_in[10];
    P.out = (__nv_bfloat16*)d_out;
    P.three = 3;
    fused_decode_kernel<<<GRID, NTHREADS, SM_TOTAL, cudaStreamPerThread>>>(map_k, map_v, P);
}
```

```cpp
#include <cuda_runtime.h>
#include <cuda_bf16.h>
#include <cuda.h>
#include <stdint.h>
#include <stdio.h>

namespace {

typedef unsigned long long u64;

constexpr int D_MODEL = 512;
constexpr int NHEAD = 32;
constexpr int SEQ = 65536;
constexpr int DH = 128;
constexpr int FF = 1792;
constexpr int GRID = 132;

constexpr int TILE = 32;
constexpr int TPH = SEQ / TILE;
constexpr int TPH_SHIFT = 11;
constexpr int NTILES = NHEAD * TPH;
constexpr int NST = 8;
constexpr int INFLIGHT = 3;
constexpr int IF_EARLY = 2;
constexpr int STAGE_BYTES = TILE * DH * 2 * 2;
constexpr int NCW = 4;
constexpr int NTHREADS = 320;

constexpr int MOD0_CTAS = 32;
constexpr int MOD_CTAS = 96;
constexpr int Q_CTAS = 128;
constexpr int FFN_CTAS = 112;

constexpr int PO_RING = 8;

constexpr int WROW = 1040;
constexpr int SM_KV = 0;
constexpr int SM_WO = SM_KV + NST * STAGE_BYTES;
constexpr int SM_WD = SM_WO + 32 * WROW;
constexpr int SM_WGU = SM_WD + 16 * WROW;
constexpr int SM_QS = SM_WGU + 512 * 64;
constexpr int SM_FL = SM_QS + 8192;
constexpr int SM_VEC = SM_FL + 2 * 4 * 132 * 4;
constexpr int SM_RED = SM_VEC + 1024;
constexpr int SM_STAT = SM_RED + 512;
constexpr int SM_FIN = SM_STAT + 64;
constexpr int SM_BAR = SM_FIN + 64;
constexpr int SM_INFO = SM_BAR + (2 * NST + 12) * 8;
constexpr int SM_TOTAL = SM_INFO + NST * 4;
static_assert(SM_TOTAL <= 232448, "shared memory budget");
static_assert(SM_BAR % 8 == 0 && SM_STAT % 16 == 0, "alignment");

__device__ unsigned g_epoch;
__device__ unsigned g_ctr;
__device__ __align__(128) u64 g_mod[1536];
__device__ __align__(128) u64 g_q[2048];
__device__ __align__(128) uint32_t g_po[PO_RING * 4 * GRID * 32];
__device__ __align__(128) uint32_t g_ph[NHEAD * GRID * 2];
__device__ __align__(128) uint32_t g_R[NHEAD * 4 * D_MODEL];
__device__ __align__(128) uint32_t g_W[8 * 32];
__device__ __align__(128) uint32_t g_f[128 * FFN_CTAS * 4];

constexpr float LOG2E = 1.4426950408889634f;
constexpr unsigned SPIN_LIMIT = 1u << 24;
constexpr unsigned WAIT_HINT_NS = 20000u;
constexpr int COMBINE_DELAY_NS = 4000;
constexpr int WL_ROUNDS = 2;
constexpr int WL_K = 2;
constexpr int R_DELAY_NS = 500;
constexpr int F_DELAY_NS = 160;
constexpr int F_DELAY2_NS = 1250;
constexpr int EG_TILES = 264;
constexpr int WREP = 8;

__device__ __forceinline__ uint32_t smem_u32(const void* p) { return (uint32_t)__cvta_generic_to_shared(p); }
__device__ __forceinline__ void mbar_init(uint32_t bar, uint32_t cnt) {
    asm volatile("mbarrier.init.shared::cta.b64 [%0], %1;" ::"r"(bar), "r"(cnt) : "memory");
}
__device__ __forceinline__ void mbar_expect_tx(uint32_t bar, uint32_t bytes) {
    asm volatile("mbarrier.arrive.expect_tx.shared::cta.b64 _, [%0], %1;" ::"r"(bar), "r"(bytes) : "memory");
}
__device__ __forceinline__ void mbar_arrive(uint32_t bar) {
    asm volatile("mbarrier.arrive.shared::cta.b64 _, [%0];" ::"r"(bar) : "memory");
}
__device__ __forceinline__ void mbar_wait(uint32_t bar, uint32_t parity) {
    unsigned spins = 0;
    while (true) {
        uint32_t ok;
        asm volatile(
            "{\n.reg .pred p;\n"
            "mbarrier.try_wait.parity.shared::cta.b64 p, [%1], %2;\n"
            "selp.u32 %0, 1, 0, p;\n}"
            : "=r"(ok)
            : "r"(bar), "r"(parity)
            : "memory");
        if (ok) break;
        if (++spins > SPIN_LIMIT) __trap();
    }
}
__device__ __forceinline__ void mbar_wait_long(uint32_t bar, uint32_t parity) {
    unsigned spins = 0;
    while (true) {
        uint32_t ok;
        asm volatile(
            "{\n.reg .pred p;\n"
            "mbarrier.try_wait.parity.shared::cta.b64 p, [%1], %2, %3;\n"
            "selp.u32 %0, 1, 0, p;\n}"
            : "=r"(ok)
            : "r"(bar), "r"(parity), "r"(WAIT_HINT_NS)
            : "memory");
        if (ok) break;
        if (++spins > SPIN_LIMIT) __trap();
    }
}
__device__ __forceinline__ uint32_t gtime32() {
    uint32_t t;
    asm volatile("mov.u32 %0, %%globaltimer_lo;" : "=r"(t)::"memory");
    return t;
}
__device__ __forceinline__ void spin_until(uint32_t t) {
    unsigned n = 0;
    while ((int)(gtime32() - t) < 0 && ++n < 256u) { }
}
__device__ __forceinline__ void hbar() { asm volatile("bar.sync 1, 128;" ::: "memory"); }

__device__ __forceinline__ void tma_tile(uint32_t dst, const CUtensorMap* m, int key, uint32_t bar, u64 pol) {
    asm volatile(
        "cp.async.bulk.tensor.3d.shared::cluster.global.mbarrier::complete_tx::bytes.L2::cache_hint "
        "[%0], [%1, {%3, %4, %3}], [%2], %5;"
        ::"r"(dst), "l"(m), "r"(bar), "r"(0), "r"(key), "l"(pol)
        : "memory");
}
__device__ __forceinline__ void bulk_g2s(uint32_t dst, const void* src, uint32_t bytes, uint32_t bar) {
    asm volatile("cp.async.bulk.shared::cluster.global.mbarrier::complete_tx::bytes [%0], [%1], %2, [%3];"
                 ::"r"(dst), "l"(src), "r"(bytes), "r"(bar) : "memory");
}
__device__ __forceinline__ void cp_async16(uint32_t dst, const void* src) {
    asm volatile("cp.async.cg.shared.global [%0], [%1], 16;" ::"r"(dst), "l"(src) : "memory");
}
__device__ __forceinline__ void cp_async16_p(uint32_t dst, const void* src, uint32_t live) {
    asm volatile("{\n.reg .pred p;\nsetp.ne.u32 p, %2, 0;\n@p cp.async.cg.shared.global.L2::256B [%0], [%1], 16;\n}" ::"r"(dst), "l"(src), "r"(live) : "memory");
}
__device__ __forceinline__ void bulk_g2s_p(uint32_t dst, const void* src, uint32_t bytes, uint32_t bar, uint32_t live) {
    asm volatile("{\n.reg .pred p;\nsetp.ne.u32 p, %4, 0;\n@p cp.async.bulk.shared::cluster.global.mbarrier::complete_tx::bytes [%0], [%1], %2, [%3];\n}"
                 ::"r"(dst), "l"(src), "r"(bytes), "r"(bar), "r"(live) : "memory");
}
__device__ __forceinline__ void mbar_expect_tx_p(uint32_t bar, uint32_t bytes, uint32_t live) {
    asm volatile("{\n.reg .pred p;\nsetp.ne.u32 p, %2, 0;\n@p mbarrier.arrive.expect_tx.shared::cta.b64 _, [%0], %1;\n}" ::"r"(bar), "r"(bytes), "r"(live) : "memory");
}
__device__ __forceinline__ void cp_async_commit() { asm volatile("cp.async.commit_group;" ::: "memory"); }
__device__ __forceinline__ void ll_store(u64* p, uint32_t data, uint32_t flag, uint32_t live = 1) {
    u64 v = ((u64)flag << 32) | data;
    asm volatile("{\n.reg .pred p;\nsetp.ne.u32 p, %2, 0;\n@p st.relaxed.gpu.global.u64 [%0], %1;\n}" ::"l"(p), "l"(v), "r"(live) : "memory");
}
__device__ __forceinline__ void ll_load(const u64* p, u64& a, uint32_t live = 1) {
    asm volatile("{\n.reg .pred p;\nsetp.ne.u32 p, %2, 0;\n@p ld.relaxed.gpu.global.u64 %0, [%1];\n}" : "+l"(a) : "l"(p), "r"(live) : "memory");
}
__device__ __forceinline__ void ll_load2(const u64* p, u64& a, u64& b, uint32_t live = 1) {
    asm volatile("{\n.reg .pred p;\nsetp.ne.u32 p, %3, 0;\n@p ld.relaxed.gpu.global.v2.u64 {%0,%1}, [%2];\n}"
                 : "+l"(a), "+l"(b) : "l"(p), "r"(live) : "memory");
}
__device__ __forceinline__ uint32_t tg_enc(float v, uint32_t tag) { return (__float_as_uint(v) & ~3u) | tag; }
__device__ __forceinline__ float tg_dec(uint32_t v) { return __uint_as_float(v & ~3u); }
__device__ __forceinline__ float tg_val(uint32_t v) { return __uint_as_float(v); }
__device__ __forceinline__ void tg_store(uint32_t* p, float v, uint32_t tag, uint32_t live = 1) {
    asm volatile("{\n.reg .pred p;\nsetp.ne.u32 p, %2, 0;\n@p st.relaxed.gpu.global.u32 [%0], %1;\n}" ::"l"(p), "r"(tg_enc(v, tag)), "r"(live) : "memory");
}
__device__ __forceinline__ void tg_store4(uint32_t* p, float a, float b, float c, float d, uint32_t tag, uint32_t live) {
    asm volatile("{\n.reg .pred p;\nsetp.ne.u32 p, %5, 0;\n@p st.relaxed.gpu.global.v4.u32 [%0], {%1,%2,%3,%4};\n}"
                 ::"l"(p), "r"(tg_enc(a, tag)), "r"(tg_enc(b, tag)), "r"(tg_enc(c, tag)), "r"(tg_enc(d, tag)), "r"(live) : "memory");
}
__device__ __forceinline__ void tg_load(const uint32_t* p, uint32_t& a, uint32_t live) {
    asm volatile("{\n.reg .pred p;\nsetp.ne.u32 p, %2, 0;\n@p ld.relaxed.gpu.global.u32 %0, [%1];\n}" : "+r"(a) : "l"(p), "r"(live) : "memory");
}
__device__ __forceinline__ void tg_load2(const uint32_t* p, uint32_t& a, uint32_t& b, uint32_t live) {
    asm volatile("{\n.reg .pred p;\nsetp.ne.u32 p, %3, 0;\n@p ld.relaxed.gpu.global.v2.u32 {%0,%1}, [%2];\n}"
                 : "+r"(a), "+r"(b) : "l"(p), "r"(live) : "memory");
}
__device__ __forceinline__ void tg_load4(const uint32_t* p, uint4& v, uint32_t live) {
    asm volatile("{\n.reg .pred p;\nsetp.ne.u32 p, %5, 0;\n@p ld.relaxed.gpu.global.v4.u32 {%0,%1,%2,%3}, [%4];\n}"
                 : "+r"(v.x), "+r"(v.y), "+r"(v.z), "+r"(v.w) : "l"(p), "r"(live) : "memory");
}
__device__ __forceinline__ uint32_t tg_bad4(const uint4& v, uint32_t tag) { return ((v.x ^ tag) | (v.y ^ tag) | (v.z ^ tag) | (v.w ^ tag)) & 3u; }
__device__ __forceinline__ bool ll_ok(u64 v, uint32_t flag) { return (uint32_t)(v >> 32) == flag; }

__device__ __forceinline__ void ldsm4(uint32_t (&r)[4], uint32_t addr) {
    asm volatile("ldmatrix.sync.aligned.m8n8.x4.shared.b16 {%0,%1,%2,%3}, [%4];"
                 : "=r"(r[0]), "=r"(r[1]), "=r"(r[2]), "=r"(r[3]) : "r"(addr) : "memory");
}
__device__ __forceinline__ void ldsm4t(uint32_t (&r)[4], uint32_t addr) {
    asm volatile("ldmatrix.sync.aligned.m8n8.x4.trans.shared.b16 {%0,%1,%2,%3}, [%4];"
                 : "=r"(r[0]), "=r"(r[1]), "=r"(r[2]), "=r"(r[3]) : "r"(addr) : "memory");
}
__device__ __forceinline__ void mma16816(float (&d)[4], const uint32_t (&a)[4], uint32_t b0, uint32_t b1) {
    asm volatile(
        "mma.sync.aligned.m16n8k16.row.col.f32.bf16.bf16.f32 {%0,%1,%2,%3}, {%4,%5,%6,%7}, {%8,%9}, {%0,%1,%2,%3};"
        : "+f"(d[0]), "+f"(d[1]), "+f"(d[2]), "+f"(d[3])
        : "r"(a[0]), "r"(a[1]), "r"(a[2]), "r"(a[3]), "r"(b0), "r"(b1));
}
__device__ __forceinline__ uint32_t movm(uint32_t a) {
    uint32_t d;
    asm volatile("movmatrix.sync.aligned.m8n8.trans.b16 %0, %1;" : "=r"(d) : "r"(a));
    return d;
}
__device__ __forceinline__ uint32_t pack_bf16(float lo, float hi) {
    uint32_t d;
    asm("cvt.rn.bf16x2.f32 %0, %1, %2;" : "=r"(d) : "f"(hi), "f"(lo));
    return d;
}
__device__ __forceinline__ float bf_lo(uint32_t v) { return __uint_as_float(v << 16); }
__device__ __forceinline__ float bf_hi(uint32_t v) { return __uint_as_float(v & 0xffff0000u); }
__device__ __forceinline__ float rbf(float x) { return bf_lo(pack_bf16(x, x)); }
__device__ __forceinline__ float ex2(float x) {
    float y;
    asm("ex2.approx.ftz.f32 %0, %1;" : "=f"(y) : "f"(x));
    return y;
}
__device__ __forceinline__ float silu_bf(float c) { return rbf(__fdividef(c, 1.f + __expf(-c))); }
__device__ __forceinline__ float4 layernorm512(float4 x, float2* stat) {
    const int tid = threadIdx.x;
    float m = ((x.x + x.y) + (x.z + x.w)) * 0.25f;
    const float d0 = x.x - m, d1 = x.y - m, d2 = x.z - m, d3 = x.w - m;
    float q = (d0 * d0 + d1 * d1) + (d2 * d2 + d3 * d3);
#pragma unroll
    for (int r = 0; r < 5; r++) {
        const float mo = __shfl_xor_sync(0xffffffffu, m, 16 >> r);
        const float qo = __shfl_xor_sync(0xffffffffu, q, 16 >> r);
        const float dl = mo - m;
        m = fmaf(dl, 0.5f, m);
        q = fmaf(dl * dl, (float)(2 << r), q + qo);
    }
    if ((tid & 31) == 0) stat[(tid >> 5) & 3] = make_float2(m, q);
    hbar();
    const float4 s01 = *reinterpret_cast<const float4*>(stat), s23 = *reinterpret_cast<const float4*>(stat + 2);
    const float da = s01.z - s01.x, db = s23.z - s23.x;
    const float ma = fmaf(da, 0.5f, s01.x), mb = fmaf(db, 0.5f, s23.x);
    const float qa = fmaf(da * da, 64.f, s01.y + s01.w), qb = fmaf(db * db, 64.f, s23.y + s23.w);
    const float dc = mb - ma;
    const float mean = rbf(fmaf(dc, 0.5f, ma));
    const float var = rbf(fmaf(dc * dc, 128.f, qa + qb) * (1.f / 512.f));
    float den;
    asm("sqrt.approx.f32 %0, %1;" : "=f"(den) : "f"(rbf(var + 1e-5f)));
    den = rbf(den);
    float4 y;
    y.x = rbf(__fdividef(rbf(x.x - mean), den));
    y.y = rbf(__fdividef(rbf(x.y - mean), den));
    y.z = rbf(__fdividef(rbf(x.z - mean), den));
    y.w = rbf(__fdividef(rbf(x.w - mean), den));
    return y;
}

__device__ __noinline__ float gemv512x32(uint32_t wbase, const uint32_t* vec, float* red) {
    const int lane = threadIdx.x & 31, hw = (threadIdx.x >> 5) & 3;
    const int g = lane >> 2, t4 = lane & 3, mi = lane >> 3, rr = lane & 7;
    float c0[2][4], c1[2][4];
#pragma unroll
    for (int i = 0; i < 2; i++) { c0[i][0] = c0[i][1] = c0[i][2] = c0[i][3] = 0.f; c1[i][0] = c1[i][1] = c1[i][2] = c1[i][3] = 0.f; }
    const int row0 = hw * 128 + (mi >> 1) * 8 + rr;
    const int sw = (row0 >> 1) & 3;
    const uint32_t a0 = wbase + row0 * 64 + (((mi & 1) ^ sw) << 4);
    const uint32_t a1 = wbase + row0 * 64 + (((2 + (mi & 1)) ^ sw) << 4);
    const uint32_t* vp = vec + hw * 64 + t4;
#pragma unroll
    for (int ks = 0; ks < 8; ks++) {
        const uint32_t b0 = vp[ks * 8], b1 = vp[ks * 8 + 4];
        uint32_t a[4];
        ldsm4t(a, a0 + ks * 1024);
        mma16816(c0[ks & 1], a, b0, b1);
        ldsm4t(a, a1 + ks * 1024);
        mma16816(c1[ks & 1], a, b0, b1);
    }
    if (t4 == 0) {
        red[hw * 32 + g] = c0[0][0] + c0[1][0];
        red[hw * 32 + 8 + g] = c0[0][2] + c0[1][2];
        red[hw * 32 + 16 + g] = c1[0][0] + c1[1][0];
        red[hw * 32 + 24 + g] = c1[0][2] + c1[1][2];
    }
    hbar();
    return (red[lane] + red[32 + lane]) + (red[64 + lane] + red[96 + lane]);
}

__device__ __forceinline__ void load_slice(uint32_t dst, const __nv_bfloat16* src, int ld, int ht) {
    const int row0 = ht >> 2, ch = ht & 3;
    uint32_t d = dst + row0 * 64 + ((ch ^ ((row0 >> 1) & 3)) << 4);
    const __nv_bfloat16* s = src + (size_t)row0 * ld + ch * 8;
#pragma unroll 4
    for (int i = 0; i < 16; i++) {
        cp_async16(d, s);
        d += 32 * 64;
        s += (size_t)32 * ld;
    }
    cp_async_commit();
}

struct Params {
    const __nv_bfloat16* x;
    const __nv_bfloat16* wq;
    const __nv_bfloat16* wo;
    const __nv_bfloat16* w_gate;
    const __nv_bfloat16* w_up;
    const __nv_bfloat16* w_down;
    const __nv_bfloat16* c;
    const __nv_bfloat16* w_mod;
    __nv_bfloat16* out;
    int three;
};

__global__ void __launch_bounds__(NTHREADS, 1)
fused_decode_kernel(const __grid_constant__ CUtensorMap map_k, const __grid_constant__ CUtensorMap map_v, const Params P) {
    extern __shared__ __align__(1024) unsigned char smem[];
    const uint32_t sb = smem_u32(smem);
    const int tid = threadIdx.x, warp = tid >> 5, lane = tid & 31;
    const int cta = blockIdx.x;

    const uint32_t bar_full = sb + SM_BAR;
    const uint32_t bar_empty = bar_full + NST * 8;
    const uint32_t bar_flf = bar_empty + NST * 8;
    const uint32_t bar_fle = bar_flf + 16;
    const uint32_t bar_w = bar_fle + 16;
    const uint32_t bar_q = bar_w + 8;
    const uint32_t bar_own = bar_q + 8;
    const uint32_t bar_done = bar_own + 8;
    const uint32_t bar_pre = bar_done + 8;
    const uint32_t bar_wl = bar_pre + 8;
    const uint32_t bar_w2 = bar_wl + 8;
    const uint32_t bar_q2 = bar_w2 + 8;
    volatile int* tile_info = reinterpret_cast<volatile int*>(smem + SM_INFO);
    uint32_t* q_s = reinterpret_cast<uint32_t*>(smem + SM_QS);
    float* fl = reinterpret_cast<float*>(smem + SM_FL);
    const int g = lane >> 2, t4 = lane & 3, mi = lane >> 3, rr = lane & 7;

    if (tid == 0) {
        if (sb & 1023) __trap();
        u64 pol;
        asm volatile("createpolicy.fractional.L2::evict_first.b64 %0, 1.0;" : "=l"(pol));
        mbar_init(bar_full, 1);
        asm volatile("fence.mbarrier_init.release.cluster;" ::: "memory");
        asm volatile("fence.proxy.async.shared::cta;" ::: "memory");
        tile_info[0] = cta;
        mbar_expect_tx(bar_full, STAGE_BYTES);
        tma_tile(sb + SM_KV, &map_k, cta * TILE, bar_full, pol);
        tma_tile(sb + SM_KV + STAGE_BYTES / 2, &map_v, cta * TILE, bar_full, pol);
    }

    if (warp == 9) {
        u64 pol;
        asm volatile("createpolicy.fractional.L2::evict_first.b64 %0, 1.0;" : "=l"(pol));
        auto issue = [&](int s, int tile) {
            tile_info[s] = tile;
            mbar_expect_tx(bar_full + 8 * s, STAGE_BYTES);
            const uint32_t dst = sb + SM_KV + s * STAGE_BYTES;
            tma_tile(dst, &map_k, tile * TILE, bar_full + 8 * s, pol);
            tma_tile(dst + STAGE_BYTES / 2, &map_v, tile * TILE, bar_full + 8 * s, pol);
        };
        if (lane == 0) {
            for (int s = 0; s < NST; s++) { if (s > 0) mbar_init(bar_full + 8 * s, 1); mbar_init(bar_empty + 8 * s, 1); }
            mbar_init(bar_flf, NCW); mbar_init(bar_flf + 8, NCW);
            mbar_init(bar_fle, 1); mbar_init(bar_fle + 8, 1);
            mbar_init(bar_w, 1);
            mbar_init(bar_q, 1);
            mbar_init(bar_own, 1);
            mbar_init(bar_done, 1);
            mbar_init(bar_pre, 1);
            mbar_init(bar_wl, 1);
            mbar_init(bar_w2, 1);
            mbar_init(bar_q2, 1);
            asm volatile("fence.mbarrier_init.release.cluster;" ::: "memory");
            asm volatile("fence.proxy.async.shared::cta;" ::: "memory");
        }
        __syncthreads();
        if (tid == 9 * 32) {
            unsigned a = cta + GRID;
            unsigned first;
            asm volatile("atom.relaxed.gpu.global.add.u32 %0, [%1], 1;" : "=r"(first) : "l"(&g_ctr) : "memory");
            int s = 1, sl = (1 + NST - INFLIGHT) % NST;
            uint32_t phe = 1, phl = 1;
            int p = 1;
            while (true) {
                const unsigned t = p >= NST ? a + NST * GRID : a;
                if (t >= (unsigned)NTILES) break;
                mbar_wait(bar_empty + 8 * s, phe);
                if (t < (unsigned)(NTILES - EG_TILES)) mbar_wait(bar_full + 8 * sl, phl);
                if (p < NST && p >= IF_EARLY) mbar_wait(bar_full + 8 * (p - IF_EARLY), 0);
                issue(s, (int)t);
                if (p + 1 < NST) a = cta + (p + 1) * GRID;
                else if (p + 1 == NST) a = first;
                else asm volatile("atom.relaxed.gpu.global.add.u32 %0, [%1], 1;" : "=r"(a) : "l"(&g_ctr) : "memory");
                if (++s == NST) { s = 0; phe ^= 1; }
                if (++sl == NST) { sl = 0; phl ^= 1; }
                p++;
            }
            const int marker = -1;
            for (int k = 0; k < NCW; k++) {
                mbar_wait(bar_empty + 8 * s, phe);
                tile_info[s] = marker;
                mbar_arrive(bar_full + 8 * s);
                if (++s == NST) { s = 0; phe ^= 1; }
            }
            const int ql = p - 1 - WL_K;
            mbar_wait(bar_full + 8 * (ql % NST), (ql / NST) & 1);
            mbar_arrive(bar_wl);
        }
        return;
    }

    if (warp == 8) {
        const uint32_t tag = (*reinterpret_cast<volatile unsigned*>(&g_epoch) + 1u) & 3u;
        __syncthreads();
#pragma unroll 1
        for (int h = 0; h < NHEAD; h++) {
            const int slot = h & 1;
            if (h >= PO_RING) {
                uint32_t w = tag;
                const uint32_t* Rp = &g_R[(size_t)((h - PO_RING) * 4 + (lane & 3)) * D_MODEL];
                unsigned spins = 0;
                while (true) {
                    tg_load(Rp, w, lane < 4);
                    if (__all_sync(0xffffffffu, ((w ^ tag) & 3u) == 0)) break;
                    if (++spins > SPIN_LIMIT) __trap();
                    __nanosleep(500);
                }
            }
            mbar_wait_long(bar_flf + 8 * slot, (h >> 1) & 1);
            const float* src = fl + slot * 4 * 132;
            const float m0 = src[128], m1 = src[132 + 128], m2 = src[264 + 128], m3 = src[396 + 128];
            const float M = fmaxf(fmaxf(m0, m1), fmaxf(m2, m3));
            const float Ms = (M == -INFINITY) ? 0.f : M;
            const float w0 = ex2((m0 - Ms) * LOG2E), w1 = ex2((m1 - Ms) * LOG2E);
            const float w2 = ex2((m2 - Ms) * LOG2E), w3 = ex2((m3 - Ms) * LOG2E);
            uint32_t* po = &g_po[((size_t)((h % PO_RING) * 4) * GRID + cta) * 32 + lane];
#pragma unroll
            for (int j = 0; j < 4; j++) {
                const int d = j * 32 + lane;
                const float ov = (w0 * src[d] + w1 * src[132 + d]) + (w2 * src[264 + d] + w3 * src[396 + d]);
                tg_store(po + j * GRID * 32, ov, (tag + h / PO_RING) & 3u);
            }
            const float lv = (w0 * src[129] + w1 * src[132 + 129]) + (w2 * src[264 + 129] + w3 * src[396 + 129]);
            if (lane < 2) tg_store(&g_ph[(h * GRID + cta) * 2 + lane], lane ? lv : M, tag);
            if (h == NHEAD - 3 && lane < 2) tg_store(&g_ph[((NHEAD - 1) * GRID + cta) * 2 + lane], 0.f, tag ^ 1u);
            __syncwarp();
            if (lane == 0) {
                mbar_arrive(bar_fle + 8 * slot);
                if (h == (cta >> 2)) mbar_arrive(bar_own);
                if (h == NHEAD - 2) mbar_arrive(bar_pre);
                if (h == NHEAD - 1) mbar_arrive(bar_done);
            }
        }
        return;
    }

    if (warp < NCW) {
        uint32_t koff[4], voff[4];
#pragma unroll
        for (int j = 0; j < 4; j++) {
            koff[j] = (mi & 1) * 1024 + rr * 128 + ((((j << 1) | (mi >> 1)) ^ rr) << 4);
            voff[j] = STAGE_BYTES / 2 + (mi >> 1) * 1024 + rr * 128 + ((((j << 1) | (mi & 1)) ^ rr) << 4);
        }
        float o[8][4];
        float m_run = -INFINITY, l_run = 0.f;
#pragma unroll
        for (int i = 0; i < 8; i++) { o[i][0] = o[i][1] = o[i][2] = o[i][3] = 0.f; }
        uint32_t qf[8][2];
#pragma unroll
        for (int kk = 0; kk < 8; kk++) { qf[kk][0] = 0x3f803f80u; qf[kk][1] = 0x3f803f80u; }
        int cur = -1;
        int s = warp % NST;
        uint32_t ph = 0;
        __syncthreads();
        bool live = (P.three != 3);
        while (true) {
            if (live) {
                mbar_wait(bar_full + 8 * s, ph);
                const int tile = tile_info[s];
                const int head = tile < 0 ? NHEAD : (tile >> TPH_SHIFT);
                if (head != cur) {
                    while (cur < head) {
                        if (cur >= 0) {
                            const int slot = cur & 1;
                            mbar_wait(bar_fle + 8 * slot, ((cur >> 1) & 1) ^ 1);
                            float* dst = fl + (slot * 4 + warp) * 132;
                            float lt = l_run;
                            lt += __shfl_xor_sync(0xffffffffu, lt, 4);
                            lt += __shfl_xor_sync(0xffffffffu, lt, 8);
                            lt += __shfl_xor_sync(0xffffffffu, lt, 16);
                            if (lane == 0) { dst[128] = m_run; dst[129] = lt; }
#pragma unroll
                            for (int i = 0; i < 8; i++)
                                if (t4 == (i & 3)) { dst[i * 16 + g] = o[i][0]; dst[i * 16 + g + 8] = o[i][2]; }
                            __syncwarp();
                            if (lane == 0) mbar_arrive(bar_flf + 8 * slot);
                        }
#pragma unroll
                        for (int i = 0; i < 8; i++) { o[i][0] = o[i][1] = o[i][2] = o[i][3] = 0.f; }
                        m_run = -INFINITY; l_run = 0.f;
                        cur++;
                    }
                    if (tile < 0) break;
                    if (cur > 0) mbar_wait(bar_q2, 0);
#pragma unroll
                    for (int kk = 0; kk < 8; kk++) { qf[kk][0] = q_s[cur * 64 + kk * 8 + t4]; qf[kk][1] = q_s[cur * 64 + kk * 8 + 4 + t4]; }
                }
            }
            const uint32_t st = sb + SM_KV + s * STAGE_BYTES;
            float sa[2][2][4];
#pragma unroll
            for (int a = 0; a < 2; a++)
#pragma unroll
                for (int b = 0; b < 2; b++) { sa[a][b][0] = sa[a][b][1] = sa[a][b][2] = sa[a][b][3] = 0.f; }
#pragma unroll
            for (int kk = 0; kk < 8; kk++) {
#pragma unroll
                for (int kg = 0; kg < 2; kg++) {
                    uint32_t a[4];
                    ldsm4(a, st + koff[kk & 3] + (kk >> 2) * 4096 + kg * 2048);
                    mma16816(sa[kg][kk & 1], a, qf[kk][0], qf[kk][1]);
                }
            }
            uint32_t va[8][4];
#pragma unroll
            for (int mt = 0; mt < 8; mt++) ldsm4t(va[mt], st + voff[mt & 3] + (mt >> 2) * 4096);
            const float scale = 0.08838834764831845f;
            const uint32_t r01 = pack_bf16(sa[0][0][0] + sa[0][1][0], sa[0][0][2] + sa[0][1][2]);
            const uint32_t r23 = pack_bf16(sa[1][0][0] + sa[1][1][0], sa[1][0][2] + sa[1][1][2]);
            const uint32_t s01 = pack_bf16(bf_lo(r01) * scale, bf_hi(r01) * scale);
            const uint32_t s23 = pack_bf16(bf_lo(r23) * scale, bf_hi(r23) * scale);
            const float s0 = bf_lo(s01), s1 = bf_hi(s01), s2 = bf_lo(s23), s3 = bf_hi(s23);
            float mx = fmaxf(fmaxf(s0, s1), fmaxf(s2, s3));
            mx = fmaxf(mx, __shfl_xor_sync(0xffffffffu, mx, 4));
            mx = fmaxf(mx, __shfl_xor_sync(0xffffffffu, mx, 8));
            mx = fmaxf(mx, __shfl_xor_sync(0xffffffffu, mx, 16));
            if (mx > m_run || !live) {
                const float corr = ex2((m_run - mx) * LOG2E);
                l_run *= corr;
#pragma unroll
                for (int i = 0; i < 8; i++) { o[i][0] *= corr; o[i][1] *= corr; o[i][2] *= corr; o[i][3] *= corr; }
                m_run = mx;
            }
            const float ml = m_run * LOG2E;
            const float p0 = ex2(fmaf(s0, LOG2E, -ml)), p1 = ex2(fmaf(s1, LOG2E, -ml));
            const float p2 = ex2(fmaf(s2, LOG2E, -ml)), p3 = ex2(fmaf(s3, LOG2E, -ml));
            l_run += (p0 + p1) + (p2 + p3);
            const uint32_t b0 = movm(pack_bf16(p0, p0)), b1 = movm(pack_bf16(p1, p1));
            const uint32_t b2 = movm(pack_bf16(p2, p2)), b3 = movm(pack_bf16(p3, p3));
#pragma unroll
            for (int mt = 0; mt < 8; mt++) mma16816(o[mt], va[mt], b0, b1);
#pragma unroll
            for (int mt = 0; mt < 8; mt++) ldsm4t(va[mt], st + voff[mt & 3] + (mt >> 2) * 4096 + 2048);
            __syncwarp();
            if (lane == 0 && live) mbar_arrive(bar_empty + 8 * s);
#pragma unroll
            for (int mt = 0; mt < 8; mt++) mma16816(o[mt], va[mt], b2, b3);
            if (live) {
                s += NCW;
                if (s >= NST) { s -= NST; ph ^= 1; }
            } else {
                mbar_wait(bar_q, 0);
                live = true;
            }
        }
        return;
    }

    const int ht = tid - 128, hw = warp - 4;
    uint32_t* vec = reinterpret_cast<uint32_t*>(smem + SM_VEC);
    float* red = reinterpret_cast<float*>(smem + SM_RED);
    float2* stat = reinterpret_cast<float2*>(smem + SM_STAT);

    const uint2 cw = reinterpret_cast<const uint2*>(P.c)[ht];
    const uint2 xw = reinterpret_cast<const uint2*>(P.x)[ht];
    const int n0 = hw * 128 + t4 * 16 + g;
    const unsigned short* xs = reinterpret_cast<const unsigned short*>(P.x) + n0;
    const unsigned short xg0 = xs[0], xg1 = xs[8], xg2 = xs[64], xg3 = xs[72];
    const uint32_t epoch = *reinterpret_cast<volatile unsigned*>(&g_epoch);
    const int qc = (cta + MOD0_CTAS) & (Q_CTAS - 1);
    if (hw == 0 && lane < 16) {
        if (cta < MOD_CTAS) ll_store(&g_mod[cta * 16 + lane], 0u, 0u);
        if (cta < Q_CTAS) ll_store(&g_q[qc * 16 + lane], 0u, 0u);
    }
    if (cta < MOD0_CTAS) load_slice(sb + SM_WGU, P.w_mod + cta * 32, 3072, ht);
    if (cta < Q_CTAS) load_slice(sb + SM_WO, P.wq + qc * 32, 4096, ht);
    uint32_t flag;
    uint2 xp;
    asm volatile("add.u32 %0, %1, 1;" : "=r"(flag) : "r"(epoch));
    asm volatile("mov.b32 %0, {%1, %2};" : "=r"(xp.x) : "h"(xg0), "h"(xg1));
    asm volatile("mov.b32 %0, {%1, %2};" : "=r"(xp.y) : "h"(xg2), "h"(xg3));
    const uint32_t sc0 = pack_bf16(silu_bf(bf_lo(cw.x)), silu_bf(bf_hi(cw.x)));
    const uint32_t sc1 = pack_bf16(silu_bf(bf_lo(cw.y)), silu_bf(bf_hi(cw.y)));
    *reinterpret_cast<uint2*>(vec + 2 * ht) = make_uint2(sc0, sc1);
    __syncthreads();
    const float4 xv = make_float4(bf_lo(xw.x), bf_hi(xw.x), bf_lo(xw.y), bf_hi(xw.y));
    const float4 ln = layernorm512(xv, stat);
    if (cta < MOD0_CTAS) {
        asm volatile("cp.async.wait_group 1;" ::: "memory");
        hbar();
        const float r = gemv512x32(sb + SM_WGU, vec, red);
        const float o2 = __shfl_xor_sync(0xffffffffu, r, 1);
        if (hw == 0 && (lane & 1) == 0) ll_store(&g_mod[cta * 16 + (lane >> 1)], pack_bf16(r, o2), flag);
    }
    asm volatile("cp.async.wait_group 0;" ::: "memory");
    {
        u64 v[4] = {0, 0, 0, 0};
        unsigned spins = 0;
        while (true) {
            ll_load2(&g_mod[2 * ht], v[0], v[1]);
            ll_load2(&g_mod[256 + 2 * ht], v[2], v[3]);
            if (ll_ok(v[0], flag) && ll_ok(v[1], flag) && ll_ok(v[2], flag) && ll_ok(v[3], flag)) break;
            if (++spins > SPIN_LIMIT) __trap();
        }
        const uint32_t s0 = (uint32_t)v[0], s1 = (uint32_t)v[1], c0 = (uint32_t)v[2], c1 = (uint32_t)v[3];
        const uint32_t h0 = pack_bf16(rbf(ln.x * rbf(1.f + bf_lo(c0))) + bf_lo(s0), rbf(ln.y * rbf(1.f + bf_hi(c0))) + bf_hi(s0));
        const uint32_t h1 = pack_bf16(rbf(ln.z * rbf(1.f + bf_lo(c1))) + bf_lo(s1), rbf(ln.w * rbf(1.f + bf_hi(c1))) + bf_hi(s1));
        hbar();
        *reinterpret_cast<uint2*>(vec + 2 * ht) = make_uint2(h0, h1);
    }
    hbar();
    if (cta < Q_CTAS) {
        const float r = gemv512x32(sb + SM_WO, vec, red);
        const float o2 = __shfl_xor_sync(0xffffffffu, r, 1);
        if (hw == 0 && (lane & 1) == 0) ll_store(&g_q[qc * 16 + (lane >> 1)], pack_bf16(r, o2), flag);
    }
    if (hw == 0) {
        u64 a = 0, b = 0;
        unsigned spins = 0;
        while (true) {
            ll_load2(&g_q[2 * lane], a, b);
            if (__all_sync(0xffffffffu, ll_ok(a, flag) && ll_ok(b, flag))) break;
            if (++spins > SPIN_LIMIT) __trap();
        }
        *reinterpret_cast<uint2*>(&q_s[2 * lane]) = make_uint2((uint32_t)a, (uint32_t)b);
        __syncwarp();
        if (lane == 0) { mbar_arrive(bar_q); }
    }
    {
        u64 v[16];
#pragma unroll
        for (int k = 0; k < 16; k++) v[k] = 0;
        unsigned spins = 0;
        while (true) {
            bool ok = true;
#pragma unroll
            for (int k = 0; k < 8; k++) ll_load2(&g_q[k * 256 + ht * 2], v[2 * k], v[2 * k + 1]);
#pragma unroll
            for (int k = 0; k < 16; k++) ok = ok && ll_ok(v[k], flag);
            if (ok) break;
            if (++spins > SPIN_LIMIT) __trap();
        }
#pragma unroll
        for (int k = 0; k < 8; k++)
            *reinterpret_cast<uint2*>(&q_s[k * 256 + ht * 2]) = make_uint2((uint32_t)v[2 * k], (uint32_t)v[2 * k + 1]);
    }
    hbar();
    if (ht == 0) mbar_arrive(bar_q2);
    if (cta >= Q_CTAS) return;

    if (cta >= MOD0_CTAS && cta < MOD_CTAS) {
        load_slice(sb + SM_WGU, P.w_mod + cta * 32, 3072, ht);
        *reinterpret_cast<uint2*>(vec + 2 * ht) = make_uint2(sc0, sc1);
        asm volatile("cp.async.wait_group 0;" ::: "memory");
        hbar();
        const float r = gemv512x32(sb + SM_WGU, vec, red);
        const float o2 = __shfl_xor_sync(0xffffffffu, r, 1);
        if (hw == 0 && (lane & 1) == 0) ll_store(&g_mod[cta * 16 + (lane >> 1)], pack_bf16(r, o2), flag);
    }
    hbar();
    asm volatile("fence.proxy.async.shared::cta;" ::: "memory");
    if (hw == 0) {
        if (lane == 0) mbar_expect_tx(bar_w, 32 * 1024);
        __syncwarp();
        bulk_g2s(sb + SM_WO + lane * WROW, P.wo + (size_t)(cta * 32 + lane) * D_MODEL, 1024, bar_w);
    }
    uint32_t md[8] = {0, 0, 0, 0, 0, 0, 0, 0};
    asm volatile("cp.async.wait_all;" ::: "memory");
    mbar_wait(bar_w, 0);
    hbar();

    const uint32_t tag = flag & 3u;
    volatile uint32_t* tgo_s = reinterpret_cast<volatile uint32_t*>(smem + SM_FIN);
    uint32_t t_go = 0;
    const int h = cta >> 2, j = cta & 3;
    const bool last_unit = (h == NHEAD - 1);
#pragma unroll 1
    for (int pass = 0; pass < P.three; pass++) {
        const uint32_t c_live = last_unit ? (pass == 2) : (pass == 1);
        if (pass == 1 && last_unit) mbar_wait_long(bar_pre, 0);
        if (pass < 2 || last_unit) {
            const uint32_t live = c_live;
            uint4 rp = make_uint4(0, 0, 0, 0);
            if (live && !last_unit) { mbar_wait_long(bar_own, 0); __nanosleep(COMBINE_DELAY_NS); }
            {
                const uint32_t* Rp = &g_R[(size_t)((h - 1) * 4 + j) * D_MODEL + 4 * ht];
                const uint32_t lv = live && h > 0;
                unsigned spins = 0;
                while (true) {
                    tg_load4(Rp, rp, lv);
                    if (__all_sync(0xffffffffu, !lv || tg_bad4(rp, tag) == 0)) break;
                    if (++spins > SPIN_LIMIT) __trap();
                    __nanosleep(500);
                }
            }
            const int sub = lane >> 3, c8 = lane & 7;
            const uint32_t* po = &g_po[((size_t)((h % PO_RING) * 4 + j) * GRID + 4 * sub + hw) * 32 + 4 * c8];
            const uint32_t* ph = &g_ph[(h * GRID + lane) * 2];
            uint32_t hm[5], hl[5];
            uint4 ov[9];
#pragma unroll
            for (int k = 0; k < 5; k++) { hm[k] = 0xff800000u | tag; hl[k] = tag; }
            const uint32_t ptag = (tag + h / PO_RING) & 3u;
#pragma unroll
            for (int i = 0; i < 9; i++) ov[i] = make_uint4(ptag, ptag, ptag, ptag);
            uint32_t wa[16][4];
#pragma unroll
            for (int i = 0; i < 8; i++) {
                const uint32_t base = sb + SM_WO + ((mi >> 1) * 8 + rr) * WROW + ((hw * 8 + i) * 16 + (mi & 1) * 8) * 2;
                ldsm4t(wa[2 * i], base);
                ldsm4t(wa[2 * i + 1], base + 16 * WROW);
            }
            if (live && last_unit) mbar_wait_long(bar_own, 0);
            unsigned spins = 0;
            uint32_t need = live ? ((lane < GRID - 128 ? 0x1fu : 0xfu) | (sub == 0 ? 0x3fe0u : 0x1fe0u)) : 0u;
            while (true) {
#pragma unroll
                for (int k = 0; k < 5; k++) tg_load2(ph + 64 * k, hm[k], hl[k], need & (1u << k));
#pragma unroll
                for (int i = 0; i < 9; i++) tg_load4(po + i * 16 * 32, ov[i], need & (32u << i));
                need = 0;
#pragma unroll
                for (int k = 0; k < 5; k++) need |= (((hm[k] ^ tag) | (hl[k] ^ tag)) & 3u) ? (1u << k) : 0u;
#pragma unroll
                for (int i = 0; i < 9; i++) need |= tg_bad4(ov[i], ptag) ? (32u << i) : 0u;
                if (!live) need = 0;
                if (!__any_sync(0xffffffffu, need != 0)) break;
                if (++spins > SPIN_LIMIT) __trap();
                if (!last_unit) __nanosleep(1000);
            }
            if (last_unit) {
                const uint32_t wv = (gtime32() & ~3u) | (live ? tag : (tag ^ 1u));
                asm volatile("{\n.reg .pred p;\nsetp.ne.u32 p, %2, 0;\n@p st.relaxed.gpu.global.u32 [%0], %1;\n}"
                             ::"l"(&g_W[(lane & (WREP - 1)) * 32 + j * 4 + hw]), "r"(wv), "r"((uint32_t)(pass > 0 && lane < WREP)) : "memory");
            }
            int mk = (int)0x807fffff;
#pragma unroll
            for (int k = 0; k < 5; k++) {
                const int b = (int)(hm[k] & ~3u);
                mk = max(mk, b ^ ((b >> 31) & 0x7fffffff));
            }
            mk = __reduce_max_sync(0xffffffffu, mk);
            const float M = __int_as_float(mk ^ ((mk >> 31) & 0x7fffffff));
            float wt[5], L = 0.f;
#pragma unroll
            for (int k = 0; k < 5; k++) {
                wt[k] = ex2((tg_dec(hm[k]) - M) * LOG2E);
                L = fmaf(wt[k], tg_dec(hl[k]), L);
            }
            float wv[9];
#pragma unroll
            for (int i = 0; i < 9; i++) wv[i] = __shfl_sync(0xffffffffu, wt[i >> 1], (16 * (i & 1) + 4 * sub + hw) & 31);
            L += __shfl_xor_sync(0xffffffffu, L, 1);
            float a0 = 0.f, a1 = 0.f, a2 = 0.f, a3 = 0.f;
#pragma unroll
            for (int i = 0; i < 9; i++) {
                a0 = fmaf(wv[i], tg_val(ov[i].x), a0); a1 = fmaf(wv[i], tg_val(ov[i].y), a1);
                a2 = fmaf(wv[i], tg_val(ov[i].z), a2); a3 = fmaf(wv[i], tg_val(ov[i].w), a3);
                if (i == 2) L += __shfl_xor_sync(0xffffffffu, L, 2);
                if (i == 6) L += __shfl_xor_sync(0xffffffffu, L, 4);
            }
            a0 += __shfl_xor_sync(0xffffffffu, a0, 8); a1 += __shfl_xor_sync(0xffffffffu, a1, 8);
            a2 += __shfl_xor_sync(0xffffffffu, a2, 8); a3 += __shfl_xor_sync(0xffffffffu, a3, 8);
            L += __shfl_xor_sync(0xffffffffu, L, 8);
            a0 += __shfl_xor_sync(0xffffffffu, a0, 16); a1 += __shfl_xor_sync(0xffffffffu, a1, 16);
            a2 += __shfl_xor_sync(0xffffffffu, a2, 16); a3 += __shfl_xor_sync(0xffffffffu, a3, 16);
            L += __shfl_xor_sync(0xffffffffu, L, 16);
            if (lane < 8) *reinterpret_cast<float4*>(red + hw * 32 + 4 * lane) = make_float4(a0, a1, a2, a3);
            hbar();
            const float of = __fdividef((red[lane] + red[32 + lane]) + (red[64 + lane] + red[96 + lane]), L);
            const uint32_t pr = pack_bf16(of, __shfl_xor_sync(0xffffffffu, of, 1));
            const uint32_t ob0 = __shfl_sync(0xffffffffu, pr, 2 * t4), ob1 = __shfl_sync(0xffffffffu, pr, 2 * t4 + 8);
            const uint32_t ob2 = __shfl_sync(0xffffffffu, pr, 2 * t4 + 16), ob3 = __shfl_sync(0xffffffffu, pr, 2 * t4 + 24);
            float y[8][4];
#pragma unroll
            for (int i = 0; i < 8; i++) {
                y[i][0] = y[i][1] = y[i][2] = y[i][3] = 0.f;
                mma16816(y[i], wa[2 * i], ob0, ob1);
            }
#pragma unroll
            for (int i = 0; i < 8; i++) mma16816(y[i], wa[2 * i + 1], ob2, ob3);
            const float ya = t4 == 0 ? y[0][0] : t4 == 1 ? y[1][0] : t4 == 2 ? y[2][0] : y[3][0];
            const float yb = t4 == 0 ? y[0][2] : t4 == 1 ? y[1][2] : t4 == 2 ? y[2][2] : y[3][2];
            const float yc = t4 == 0 ? y[4][0] : t4 == 1 ? y[5][0] : t4 == 2 ? y[6][0] : y[7][0];
            const float yd = t4 == 0 ? y[4][2] : t4 == 1 ? y[5][2] : t4 == 2 ? y[6][2] : y[7][2];
            uint32_t* Rn = &g_R[(size_t)(h * 4 + j) * D_MODEL + 4 * ht];
            const uint32_t stag = live ? tag : (tag ^ 1u), sl = pass > 0;
            tg_store4(Rn, tg_val(rp.x) + ya, tg_val(rp.y) + yb, tg_val(rp.z) + yc, tg_val(rp.w) + yd, stag, sl);
        }
        if (pass == 1) {
            mbar_wait_long(bar_pre, 0);
            u64 v[16];
#pragma unroll
            for (int k = 0; k < 16; k++) v[k] = 0;
            unsigned spins = 0;
            while (true) {
                bool ok = true;
#pragma unroll
                for (int k = 0; k < 16; k++)
                    ll_load(&g_mod[(2 + (k >> 2)) * 256 + (n0 >> 1) + ((k & 1) ? 4 : 0) + ((k & 2) ? 32 : 0)], v[k]);
#pragma unroll
                for (int k = 0; k < 16; k++) ok = ok && ll_ok(v[k], flag);
                if (ok) break;
                if (++spins > SPIN_LIMIT) __trap();
                __nanosleep(500);
            }
            const uint32_t sel = (g & 1) ? 0x7632u : 0x5410u;
#pragma unroll
            for (int k = 0; k < 8; k++) md[k] = __byte_perm((uint32_t)v[2 * k], (uint32_t)v[2 * k + 1], sel);
        }
        const uint32_t live = (pass == 2);
        if (cta < FFN_CTAS) {
            if (live) mbar_wait_long(bar_wl, 0);
            const int row0 = ht >> 2, ch = ht & 3;
            uint32_t d = sb + SM_WGU + row0 * 64 + ((ch ^ ((row0 >> 1) & 3)) << 4);
            const __nv_bfloat16* s = (ch < 2 ? P.w_gate : P.w_up) + (size_t)row0 * FF + cta * 16 + (ch & 1) * 8;
#pragma unroll 1
            for (int r = 0; r < WL_ROUNDS; r++) {
#pragma unroll
                for (int i = 0; i < 16 / WL_ROUNDS; i++) {
                    cp_async16_p(d, s, live);
                    d += 32 * 64;
                    s += (size_t)32 * FF;
                }
                cp_async_commit();
                if (r == 0 && hw == 0) {
                    mbar_expect_tx_p(bar_w2, 16 * 1024, live && lane == 0);
                    __syncwarp();
                    bulk_g2s_p(sb + SM_WD + lane * WROW, P.w_down + (size_t)(cta * 16 + (lane & 15)) * D_MODEL, 1024, bar_w2, live && lane < 16);
                }
                if (r + 1 < WL_ROUNDS) asm volatile("cp.async.wait_group 0;" ::: "memory");
            }
        }
        uint32_t ga[8][4], ua[8][4], da[8][4];
        {
            if (cta < FFN_CTAS) {
                asm volatile("cp.async.wait_all;" ::: "memory");
                hbar();
            }
            const int row0 = hw * 128 + (mi >> 1) * 8 + rr;
            const int sw = (row0 >> 1) & 3;
            const uint32_t a0 = sb + SM_WGU + row0 * 64 + (((mi & 1) ^ sw) << 4);
            const uint32_t a1 = sb + SM_WGU + row0 * 64 + (((2 + (mi & 1)) ^ sw) << 4);
#pragma unroll
            for (int ks = 0; ks < 8; ks++) { ldsm4t(ga[ks], a0 + ks * 1024); ldsm4t(ua[ks], a1 + ks * 1024); }
            if (live && cta < FFN_CTAS) mbar_wait(bar_w2, 0);
#pragma unroll
            for (int i = 0; i < 8; i++)
                ldsm4t(da[i], sb + SM_WD + ((mi >> 1) * 8 + rr) * WROW + ((hw * 8 + i) * 16 + (mi & 1) * 8) * 2);
        }
        float4 x1;
        {
            uint4 v[4];
#pragma unroll
            for (int k = 0; k < 4; k++) v[k] = make_uint4(0, 0, 0, 0);
            const uint32_t* R = &g_R[(size_t)((NHEAD - 1) * 4) * D_MODEL + 4 * ht];
            if (live) mbar_wait_long(bar_done, 0);
            unsigned spins = 0;
            if (hw == 0) {
                uint32_t w = tag;
                const uint32_t* Wp = &g_W[(cta & (WREP - 1)) * 32 + (lane & 15)];
                const uint32_t lv = live && lane < 16;
                while (true) {
                    tg_load(Wp, w, lv);
                    if (__all_sync(0xffffffffu, ((w ^ tag) & 3u) == 0)) break;
                    if (++spins > SPIN_LIMIT) __trap();
                }
                const uint32_t now = gtime32();
                int dl = lv ? (int)((w & ~3u) - now) : -1000000;
                dl = __reduce_max_sync(0xffffffffu, dl);
                dl = min(dl, 0);
                if (lane == 0) *tgo_s = now + (uint32_t)dl + R_DELAY_NS;
            }
            hbar();
            t_go = *tgo_s;
            if (live) spin_until(t_go);
            spins = 0;
            uint32_t need = (live && (cta < FFN_CTAS || ht == cta)) ? 0xfu : 0u;
            const uint32_t lr = need;
#pragma unroll
            for (int k = 0; k < 4; k++) tg_load4(R + k * D_MODEL, v[k], need & (1u << k));
            while (true) {
                need = 0;
#pragma unroll
                for (int k = 0; k < 4; k++) need |= tg_bad4(v[k], tag) ? (1u << k) : 0u;
                need &= lr;
                if (!__any_sync(0xffffffffu, need != 0)) break;
                if (++spins > SPIN_LIMIT) __trap();
#pragma unroll
                for (int k = 0; k < 4; k++) tg_load4(R + k * D_MODEL, v[k], need & (1u << k));
            }
            const float a0 = (tg_val(v[0].x) + tg_val(v[1].x)) + (tg_val(v[2].x) + tg_val(v[3].x));
            const float a1 = (tg_val(v[0].y) + tg_val(v[1].y)) + (tg_val(v[2].y) + tg_val(v[3].y));
            const float a2 = (tg_val(v[0].z) + tg_val(v[1].z)) + (tg_val(v[2].z) + tg_val(v[3].z));
            const float a3 = (tg_val(v[0].w) + tg_val(v[1].w)) + (tg_val(v[2].w) + tg_val(v[3].w));
            x1.x = rbf(bf_lo(xp.x) + rbf(bf_lo(md[0]) * rbf(a0)));
            x1.y = rbf(bf_hi(xp.x) + rbf(bf_hi(md[0]) * rbf(a1)));
            x1.z = rbf(bf_lo(xp.y) + rbf(bf_lo(md[1]) * rbf(a2)));
            x1.w = rbf(bf_hi(xp.y) + rbf(bf_hi(md[1]) * rbf(a3)));
        }
        if (cta < FFN_CTAS) {
            const float4 y = layernorm512(x1, stat);
            const uint32_t h0 = pack_bf16(rbf(y.x * rbf(1.f + bf_lo(md[4]))) + bf_lo(md[2]), rbf(y.y * rbf(1.f + bf_hi(md[4]))) + bf_hi(md[2]));
            const uint32_t h1 = pack_bf16(rbf(y.z * rbf(1.f + bf_lo(md[5]))) + bf_lo(md[3]), rbf(y.w * rbf(1.f + bf_hi(md[5]))) + bf_hi(md[3]));
            {
                unsigned short* v16 = reinterpret_cast<unsigned short*>(vec) + n0;
                v16[0] = (unsigned short)h0; v16[8] = (unsigned short)(h0 >> 16);
                v16[64] = (unsigned short)h1; v16[72] = (unsigned short)(h1 >> 16);
            }
            __syncwarp();
            float c0[4][4], c1[4][4];
#pragma unroll
            for (int i = 0; i < 4; i++) { c0[i][0] = c0[i][1] = c0[i][2] = c0[i][3] = 0.f; c1[i][0] = c1[i][1] = c1[i][2] = c1[i][3] = 0.f; }
            const uint32_t* vp = vec + hw * 64 + t4;
            uint32_t bf[8][2];
#pragma unroll
            for (int ks = 0; ks < 8; ks++) { bf[ks][0] = vp[ks * 8]; bf[ks][1] = vp[ks * 8 + 4]; }
#pragma unroll
            for (int ks = 0; ks < 8; ks++) {
                mma16816(c0[ks & 3], ga[ks], bf[ks][0], bf[ks][1]);
                mma16816(c1[ks & 3], ua[ks], bf[ks][0], bf[ks][1]);
            }
            if (t4 == 0) {
                red[hw * 32 + g] = (c0[0][0] + c0[1][0]) + (c0[2][0] + c0[3][0]);
                red[hw * 32 + 8 + g] = (c0[0][2] + c0[1][2]) + (c0[2][2] + c0[3][2]);
                red[hw * 32 + 16 + g] = (c1[0][0] + c1[1][0]) + (c1[2][0] + c1[3][0]);
                red[hw * 32 + 24 + g] = (c1[0][2] + c1[1][2]) + (c1[2][2] + c1[3][2]);
            }
            hbar();
            const float gx = rbf((red[lane] + red[32 + lane]) + (red[64 + lane] + red[96 + lane]));
            const float uu = __shfl_down_sync(0xffffffffu, gx, 16);
            const float inner = 0.7978845608028654f * (gx + 0.044715f * gx * gx * gx);
            const float ge = rbf(__fdividef(gx, 1.f + ex2(-2.f * LOG2E * inner)));
            const float act = rbf(ge * uu);
            const uint32_t ap = pack_bf16(act, __shfl_xor_sync(0xffffffffu, act, 1));
            const uint32_t ab0 = __shfl_sync(0xffffffffu, ap, 2 * t4), ab1 = __shfl_sync(0xffffffffu, ap, 2 * t4 + 8);
            float f[8][4];
#pragma unroll
            for (int i = 0; i < 8; i++) {
                f[i][0] = f[i][1] = f[i][2] = f[i][3] = 0.f;
                mma16816(f[i], da[i], ab0, ab1);
            }
            const float fa = t4 == 0 ? f[0][0] : t4 == 1 ? f[1][0] : t4 == 2 ? f[2][0] : f[3][0];
            const float fb = t4 == 0 ? f[0][2] : t4 == 1 ? f[1][2] : t4 == 2 ? f[2][2] : f[3][2];
            const float fc = t4 == 0 ? f[4][0] : t4 == 1 ? f[5][0] : t4 == 2 ? f[6][0] : f[7][0];
            const float fd = t4 == 0 ? f[4][2] : t4 == 1 ? f[5][2] : t4 == 2 ? f[6][2] : f[7][2];
            tg_store4(&g_f[((ht >> 1) * FFN_CTAS + cta) * 8 + (ht & 1) * 4], fa, fb, fc, fd, live ? tag : (tag ^ 1u), pass > 0);
        }
        if (hw == (cta >> 5)) {
            uint4 v[4];
#pragma unroll
            for (int k = 0; k < 4; k++) v[k] = make_uint4(tag, tag, tag, tag);
            const uint32_t* src = &g_f[((cta >> 1) * FFN_CTAS + lane) * 8 + (cta & 1) * 4];
            unsigned spins = 0;
            uint32_t need = live ? (lane < FFN_CTAS - 96 ? 0xfu : 0x7u) : 0u;
            if (live) spin_until(cta < FFN_CTAS ? gtime32() + F_DELAY_NS : t_go + F_DELAY2_NS);
            while (true) {
#pragma unroll
                for (int k = 0; k < 4; k++) tg_load4(src + k * 32 * 8, v[k], need & (1u << k));
                need = 0;
#pragma unroll
                for (int k = 0; k < 4; k++) need |= tg_bad4(v[k], tag) ? (1u << k) : 0u;
                if (!live) need = 0;
                if (!__any_sync(0xffffffffu, need != 0)) break;
                if (++spins > SPIN_LIMIT) __trap();
            }
            float s0 = (tg_val(v[0].x) + tg_val(v[1].x)) + (tg_val(v[2].x) + tg_val(v[3].x));
            float s1 = (tg_val(v[0].y) + tg_val(v[1].y)) + (tg_val(v[2].y) + tg_val(v[3].y));
            float s2 = (tg_val(v[0].z) + tg_val(v[1].z)) + (tg_val(v[2].z) + tg_val(v[3].z));
            float s3 = (tg_val(v[0].w) + tg_val(v[1].w)) + (tg_val(v[2].w) + tg_val(v[3].w));
#pragma unroll
            for (int o2 = 1; o2 < 32; o2 <<= 1) {
                s0 += __shfl_xor_sync(0xffffffffu, s0, o2);
                s1 += __shfl_xor_sync(0xffffffffu, s1, o2);
                s2 += __shfl_xor_sync(0xffffffffu, s2, o2);
                s3 += __shfl_xor_sync(0xffffffffu, s3, o2);
            }
            if (ht == cta) {
                const uint32_t o0 = pack_bf16(x1.x + rbf(bf_lo(md[6]) * rbf(s0)), x1.y + rbf(bf_hi(md[6]) * rbf(s1)));
                const uint32_t o1 = pack_bf16(x1.z + rbf(bf_lo(md[7]) * rbf(s2)), x1.w + rbf(bf_hi(md[7]) * rbf(s3)));
                unsigned short* o16 = reinterpret_cast<unsigned short*>(P.out) + n0;
                asm volatile("{\n.reg .pred p;\nsetp.ne.u32 p, %5, 0;\n"
                             "@p st.global.b16 [%0], %1;\n@p st.global.b16 [%0+16], %2;\n@p st.global.b16 [%0+128], %3;\n@p st.global.b16 [%0+144], %4;\n}"
                             ::"l"(o16), "h"((unsigned short)o0), "h"((unsigned short)(o0 >> 16)), "h"((unsigned short)o1), "h"((unsigned short)(o1 >> 16)), "r"(live) : "memory");
                asm volatile("{\n.reg .pred p;\nsetp.ne.u32 p, %3, 0;\n@p st.global.u32 [%0], 0;\n@p st.global.u32 [%1], %2;\n}"
                             ::"l"(&g_ctr), "l"(&g_epoch), "r"(flag), "r"((uint32_t)(live && cta == 0)) : "memory");
            }
        }
        if (pass < 2) hbar();
    }
}

typedef CUresult (*EncodeTiledFn)(CUtensorMap*, CUtensorMapDataType, cuuint32_t, void*, const cuuint64_t*, const cuuint64_t*,
                                  const cuuint32_t*, const cuuint32_t*, CUtensorMapInterleave, CUtensorMapSwizzle,
                                  CUtensorMapL2promotion, CUtensorMapFloatOOBfill);

bool make_kv_map(EncodeTiledFn enc, CUtensorMap* m, void* base) {
    cuuint64_t gd[3] = {64, (cuuint64_t)NHEAD * SEQ, 2};
    cuuint64_t gs[2] = {256, 128};
    cuuint32_t bd[3] = {64, TILE, 2};
    cuuint32_t es[3] = {1, 1, 1};
    return enc(m, CU_TENSOR_MAP_DATA_TYPE_BFLOAT16, 3, base, gd, gs, bd, es, CU_TENSOR_MAP_INTERLEAVE_NONE,
               CU_TENSOR_MAP_SWIZZLE_128B, CU_TENSOR_MAP_L2_PROMOTION_L2_256B, CU_TENSOR_MAP_FLOAT_OOB_FILL_NONE) == CUDA_SUCCESS;
}

}

extern "C" void kernel_launch(void* const* d_in, const int* in_sizes, int n_in, void* d_out, int out_size) {
    (void)in_sizes; (void)n_in; (void)out_size;
    static EncodeTiledFn enc = nullptr;
    static CUtensorMap map_k, map_v;
    static void *k_ptr = nullptr, *v_ptr = nullptr;
    if (!enc) {
        void* fn = nullptr;
        cudaDriverEntryPointQueryResult qr;
        if (cudaGetDriverEntryPoint("cuTensorMapEncodeTiled", &fn, cudaEnableDefault, &qr) != cudaSuccess || !fn) {
            fprintf(stderr, "cuTensorMapEncodeTiled not available\n");
            return;
        }
        enc = (EncodeTiledFn)fn;
        cudaFuncSetAttribute(fused_decode_kernel, cudaFuncAttributeMaxDynamicSharedMemorySize, SM_TOTAL);
    }
    if (k_ptr != d_in[1] || v_ptr != d_in[2]) {
        if (!make_kv_map(enc, &map_k, d_in[1]) || !make_kv_map(enc, &map_v, d_in[2])) {
            fprintf(stderr, "tensor map encode failed\n");
            return;
        }
        k_ptr = d_in[1];
        v_ptr = d_in[2];
    }
    Params P;
    P.x = (const __nv_bfloat16*)d_in[0];
    P.wq = (const __nv_bfloat16*)d_in[3];
    P.wo = (const __nv_bfloat16*)d_in[4];
    P.w_gate = (const __nv_bfloat16*)d_in[6];
    P.w_up = (const __nv_bfloat16*)d_in[7];
    P.w_down = (const __nv_bfloat16*)d_in[8];
    P.c = (const __nv_bfloat16*)d_in[9];
    P.w_mod = (const __nv_bfloat16*)d_in[10];
    P.out = (__nv_bfloat16*)d_out;
    P.three = 3;
    fused_decode_kernel<<<GRID, NTHREADS, SM_TOTAL, cudaStreamPerThread>>>(map_k, map_v, P);
}
```
